```python
import torch

def _softmax(x, axis=-1):
    return torch.softmax(x, dim=axis)
def _gelu(x):
    return torch.nn.functional.gelu(x, approximate="tanh")
def _silu(x):
    return torch.nn.functional.silu(x)
def _sigmoid(x):
    return torch.sigmoid(x)
def _layernorm(x, axis=-1, eps=1e-5):
    m = x.mean(dim=axis, keepdim=True)
    v = x.var(dim=axis, keepdim=True, unbiased=False)
    return (x - m) / torch.sqrt(v + eps)
def _scatter_add(tgt, idx, src, axis=0):
    return tgt.clone().index_add_(axis, idx, src)
def _segment_sum(src, seg, n):
    out = torch.zeros((n,) + src.shape[1:], dtype=src.dtype)
    return out.index_add_(0, seg, src)
def _pad(x, pw):
    flat = tuple(v for pair in reversed(pw) for v in pair)
    return torch.nn.functional.pad(x, flat)

kernel_name = 'recurrent_scan__gqa_block_cached__glu_gated_glu__decode'

def setup_inputs():

    _w = (lambda a: (lambda t: t.to(torch.bfloat16) if t.is_floating_point() else t)(torch.as_tensor(a)))
    def _A_setup():
        B, Sq, D = 8, 1, 512
        Hq, Hkv, Sk, Dh = 32, 8, 4096, 128
        assert Hq % Hkv == 0, (Hq, Hkv)
        return {
            "x": _w((lambda *s: torch.randn(*s, dtype=torch.bfloat16) * 0.05)(B, Sq, D)),
            "k_cache": _w((lambda *s: torch.randn(*s, dtype=torch.bfloat16) * 1.6)(B, Hkv, Sk, Dh)),
            "v_cache": _w((lambda *s: torch.randn(*s, dtype=torch.bfloat16) * 0.2)(B, Hkv, Sk, Dh)),
            "wq": _w((lambda *s: torch.randn(*s, dtype=torch.bfloat16) * 1.6)(D, Hq * Dh) * (D ** -0.5)),
            "wo": _w((lambda *s: torch.randn(*s, dtype=torch.bfloat16) * 0.2)(Hq * Dh, D) * ((Hq * Dh) ** -0.5)),
        }
    _A_in = _A_setup()

    def _B_setup():
        B, S, D, F = 8, 1, 512, 1792
        return {
            "x": _w((lambda *s: torch.randn(*s, dtype=torch.bfloat16) * 0.05)(B, S, D)),
            "w_gate": _w((lambda *s: torch.randn(*s, dtype=torch.bfloat16) * 1.6)(D, F)),
            "w_up": _w((lambda *s: torch.randn(*s, dtype=torch.bfloat16) * 0.1)(D, F)),
            "w_down": _w((lambda *s: torch.randn(*s, dtype=torch.bfloat16) * 0.1)(F, D)),
        }
    _B_in = _B_setup()

    return {
        "A_x": _A_in["x"],
        "A_k_cache": _A_in["k_cache"],
        "A_v_cache": _A_in["v_cache"],
        "A_wq": _A_in["wq"],
        "A_wo": _A_in["wo"],
        "B_x": _B_in["x"],
        "B_w_gate": _B_in["w_gate"],
        "B_w_up": _B_in["w_up"],
        "B_w_down": _B_in["w_down"],
    }

def reference(A_x, A_k_cache, A_v_cache, A_wq, A_wo, B_x, B_w_gate, B_w_up, B_w_down):
    def _A_ref(x, k_cache, v_cache, wq, wo):
        B, Sq, D = x.shape
        Hq, Dh = 32, 128
        Hkv = k_cache.shape[1]
        rep = Hq // Hkv
        q = (lambda x, *d: x.permute(*d))((x @ wq).reshape(B, Sq, Hq, Dh), 0, 2, 1, 3)
        k = (lambda x, n, axis: torch.repeat_interleave(x, n, dim=axis))(k_cache, rep, axis=1)
        v = (lambda x, n, axis: torch.repeat_interleave(x, n, dim=axis))(v_cache, rep, axis=1)
        scores = torch.einsum("bhqd,bhkd->bhqk", q, k) * (Dh ** -0.5)
        p = _softmax(scores, axis=-1)
        o = torch.einsum("bhqk,bhkd->bhqd", p, v)
        return (lambda x, *d: x.permute(*d))(o, 0, 2, 1, 3).reshape(B, Sq, Hq * Dh) @ wo

    def _B_ref(x, w_gate, w_up, w_down):
        g = torch.einsum("bsd,df->bsf", x, w_gate)
        u = torch.einsum("bsd,df->bsf", x, w_up)
        h = _sigmoid(g) * u
        return torch.einsum("bsf,fd->bsd", h, w_down)

    x = A_x
    xn = _layernorm(x, axis=-1)
    s = _A_ref(xn, A_k_cache, A_v_cache, A_wq, A_wo)
    g = _silu(_B_ref(xn, B_w_gate, B_w_up, B_w_down))
    return x + s * g
```

```cpp
#include <cuda.h>
#include <cuda_bf16.h>
#include <cuda_runtime.h>
#include <stdint.h>

namespace {

constexpr int DM = 512, FF = 1792;
constexpr int N_ATT = 128, N_FFN = 4, GRID = N_ATT + N_FFN;
constexpr int N_THREADS = 320;
constexpr int STAGE = 16384, NSLOT = 10;
constexpr int N_STEPS = 16;
constexpr int KV_ITEMS = 4 * N_STEPS;
constexpr int FFN_ITEMS = 56;
constexpr int WD_ROWS = FF / 16;

#define WIN_HEAD 3
#define WIN_BODY 4
#define WIN_TAIL 10
#define HEAD_ITEMS 6
#define TAIL_ITEMS 10
#define GATE_LEFT 384
#define MARK_STEP 14
#define WQ_PROMO CU_TENSOR_MAP_L2_PROMOTION_NONE
#define WIN_FFN 5
#define LAG_1 64
#define LAG_2 192
#define LEAD_1 64
#define WARM 1

constexpr int OFF_W = NSLOT * STAGE;
constexpr int OFF_XN = OFF_W + 49152;
constexpr int XN_STRIDE = 1040;
constexpr int OFF_Q = OFF_XN + 8 * XN_STRIDE;
constexpr int OFF_O = OFF_Q + 4 * 272;
constexpr int O_STRIDE = 528;
constexpr int OFF_H = OFF_O + 8 * O_STRIDE;
constexpr int H_STRIDE = 240;
constexpr int OFF_STAT = OFF_H + 8 * H_STRIDE;
constexpr int OFF_FIN = OFF_STAT + 256;
constexpr int OFF_BAR = OFF_FIN + 1024;
constexpr int OFF_CTL = OFF_BAR + 240;
constexpr int OFF_PROBE = OFF_BAR + 256;
constexpr int SMEM_BYTES = OFF_PROBE + 256 + 1024;

constexpr float LOG2E = 1.4426950408889634f;
constexpr float QK_SCALE = 0.08838834764831845f;
constexpr uint32_t SPIN_LIMIT = 1u << 24;

enum { MAP_K, MAP_V, MAP_WQ, MAP_WG, MAP_WU, MAP_WD, MAP_WO, N_MAPS };
struct Maps { CUtensorMap m[N_MAPS]; };

__device__ uint32_t g_epoch[GRID];
__device__ uint32_t g_progress;
__device__ unsigned long long g_q[8 * 2048];
__device__ unsigned long long g_h[8 * (FF / 2)];
__device__ __align__(128) uint32_t g_opart[32 * 8 * 2 * 128];
__device__ __align__(128) uint32_t g_stat[32 * 8 * 4];
__device__ __align__(128) uint32_t g_part[2 * 16 * DM * 8];
#define PROBE_AT(warp, i)
#define PROBE_ANCHOR(i)
#define PROBE_DUMP()

__device__ __forceinline__ void mbar_init(uint32_t bar, uint32_t count) {
    asm volatile("mbarrier.init.shared::cta.b64 [%0], %1;" ::"r"(bar), "r"(count) : "memory");
}
__device__ __forceinline__ void mbar_expect_tx(uint32_t bar, uint32_t bytes) {
    asm volatile("mbarrier.arrive.expect_tx.shared::cta.b64 _, [%0], %1;" ::"r"(bar), "r"(bytes) : "memory");
}
__device__ __forceinline__ void mbar_arrive(uint32_t bar) {
    asm volatile("mbarrier.arrive.shared::cta.b64 _, [%0];" ::"r"(bar) : "memory");
}
__device__ __forceinline__ uint32_t mbar_test(uint32_t bar, uint32_t parity) {
    uint32_t ok;
    asm volatile("{\n.reg .pred p;\nmbarrier.test_wait.parity.shared::cta.b64 p, [%1], %2;\nselp.u32 %0, 1, 0, p;\n}"
                 : "=r"(ok) : "r"(bar), "r"(parity) : "memory");
    return ok;
}
__device__ __forceinline__ void mbar_wait(uint32_t bar, uint32_t parity) {
    uint32_t ok, spins = 0;
    do {
        asm volatile("{\n.reg .pred p;\nmbarrier.try_wait.parity.shared::cta.b64 p, [%1], %2;\nselp.u32 %0, 1, 0, p;\n}"
                     : "=r"(ok) : "r"(bar), "r"(parity) : "memory");
        if (++spins > SPIN_LIMIT) __trap();
    } while (!ok);
}
__device__ __forceinline__ void tma_load(uint32_t dst, const CUtensorMap* m, int c0, int c1, uint32_t bar) {
    asm volatile("cp.async.bulk.tensor.3d.shared::cluster.global.mbarrier::complete_tx::bytes [%0], [%1, {%3, %4, %5}], [%2];"
                 ::"r"(dst), "l"(m), "r"(bar), "r"(c0), "r"(c1), "r"(0) : "memory");
}
__device__ __forceinline__ void consumer_sync() { asm volatile("bar.sync 1, 256;" ::: "memory"); }
__device__ __forceinline__ void ldsm4(uint32_t (&r)[4], uint32_t addr) {
    asm volatile("ldmatrix.sync.aligned.m8n8.x4.shared.b16 {%0,%1,%2,%3}, [%4];"
                 : "=r"(r[0]), "=r"(r[1]), "=r"(r[2]), "=r"(r[3]) : "r"(addr) : "memory");
}
__device__ __forceinline__ void ldsm2(uint32_t& r0, uint32_t& r1, uint32_t addr) {
    asm volatile("ldmatrix.sync.aligned.m8n8.x2.shared.b16 {%0,%1}, [%2];" : "=r"(r0), "=r"(r1) : "r"(addr) : "memory");
}
__device__ __forceinline__ void ldsm4t(uint32_t (&r)[4], uint32_t addr) {
    asm volatile("ldmatrix.sync.aligned.m8n8.x4.trans.shared.b16 {%0,%1,%2,%3}, [%4];"
                 : "=r"(r[0]), "=r"(r[1]), "=r"(r[2]), "=r"(r[3]) : "r"(addr) : "memory");
}
__device__ __forceinline__ void mma(float (&c)[4], uint32_t a0, uint32_t a1, uint32_t a2, uint32_t a3, uint32_t b0, uint32_t b1) {
    asm volatile("mma.sync.aligned.m16n8k16.row.col.f32.bf16.bf16.f32 {%0,%1,%2,%3}, {%4,%5,%6,%7}, {%8,%9}, {%0,%1,%2,%3};"
                 : "+f"(c[0]), "+f"(c[1]), "+f"(c[2]), "+f"(c[3])
                 : "r"(a0), "r"(a1), "r"(a2), "r"(a3), "r"(b0), "r"(b1));
}
__device__ __forceinline__ uint32_t transpose8x8(uint32_t a) {
    uint32_t d;
    asm volatile("movmatrix.sync.aligned.m8n8.trans.b16 %0, %1;" : "=r"(d) : "r"(a));
    return d;
}
__device__ __forceinline__ uint32_t pack_bf16(float lo, float hi) {
    uint32_t d;
    asm("cvt.rn.bf16x2.f32 %0, %1, %2;" : "=r"(d) : "f"(hi), "f"(lo));
    return d;
}
__device__ __forceinline__ float bf_lo(uint32_t v) { return __uint_as_float(v << 16); }
__device__ __forceinline__ float bf_hi(uint32_t v) { return __uint_as_float(v & 0xffff0000u); }
__device__ __forceinline__ float round_bf16(float v) { return bf_lo(pack_bf16(v, 0.f)); }
__device__ __forceinline__ uint32_t max_bf16x2(uint32_t a, uint32_t b) {
    uint32_t d;
    asm("max.bf16x2 %0, %1, %2;" : "=r"(d) : "r"(a), "r"(b));
    return d;
}
__device__ __forceinline__ float ex2(float x) {
    float y;
    asm("ex2.approx.ftz.f32 %0, %1;" : "=f"(y) : "f"(x));
    return y;
}
__device__ __forceinline__ float rcp(float x) {
    float y;
    asm("rcp.approx.ftz.f32 %0, %1;" : "=f"(y) : "f"(x));
    return y;
}
__device__ __forceinline__ float sqrt_approx(float x) {
    float y;
    asm("sqrt.approx.ftz.f32 %0, %1;" : "=f"(y) : "f"(x));
    return y;
}
__device__ __forceinline__ float sigmoid(float x) { return rcp(1.f + ex2(-x * LOG2E)); }
__device__ __forceinline__ void sts32(uint32_t addr, uint32_t v) { asm volatile("st.shared.b32 [%0], %1;" ::"r"(addr), "r"(v) : "memory"); }
__device__ __forceinline__ void sts64(uint32_t addr, uint32_t a, uint32_t b) { asm volatile("st.shared.v2.b32 [%0], {%1,%2};" ::"r"(addr), "r"(a), "r"(b) : "memory"); }
__device__ __forceinline__ uint32_t lds32(uint32_t addr) {
    uint32_t v;
    asm volatile("ld.shared.b32 %0, [%1];" : "=r"(v) : "r"(addr) : "memory");
    return v;
}
__device__ __forceinline__ float2 lds64f(uint32_t addr) {
    float2 v;
    asm volatile("ld.shared.v2.f32 {%0,%1}, [%2];" : "=f"(v.x), "=f"(v.y) : "r"(addr) : "memory");
    return v;
}

__device__ __forceinline__ void sts64_if(uint32_t on, uint32_t addr, float a, float b) {
    asm volatile("{\n.reg .pred p;\nsetp.ne.u32 p, %0, 0;\n@p st.shared.v2.f32 [%1], {%2,%3};\n}" ::"r"(on), "r"(addr), "f"(a), "f"(b) : "memory");
}

__device__ __forceinline__ void put_pair(unsigned long long* p, uint32_t data, uint32_t epoch) {
    asm volatile("st.relaxed.gpu.global.b64 [%0], %1;" ::"l"(p), "l"(((unsigned long long)epoch << 32) | data) : "memory");
}
__device__ __forceinline__ void ld_pair(uint32_t on, unsigned long long& v, const unsigned long long* p) {
    asm volatile("{\n.reg .pred p;\nsetp.ne.u32 p, %2, 0;\n@p ld.relaxed.gpu.global.b64 %0, [%1];\n}" : "+l"(v) : "l"(p), "r"(on) : "memory");
}
__device__ __forceinline__ uint32_t get_pair(unsigned long long v, const unsigned long long* p, uint32_t epoch) {
    uint32_t spins = 0;
    while ((uint32_t)(v >> 32) != epoch) {
        ld_pair(1, v, p);
        if (++spins > SPIN_LIMIT) __trap();
    }
    return (uint32_t)v;
}
__device__ __forceinline__ uint32_t tagged(float v, uint32_t tag) { return (__float_as_uint(v) & ~3u) | tag; }
__device__ __forceinline__ void put1(uint32_t on, uint32_t* p, float a, uint32_t tag) {
    asm volatile("{\n.reg .pred p;\nsetp.ne.u32 p, %0, 0;\n@p st.relaxed.gpu.global.b32 [%1], %2;\n}" ::"r"(on), "l"(p), "r"(tagged(a, tag)) : "memory");
}
__device__ __forceinline__ void put2(uint32_t on, uint32_t* p, float a, float b, uint32_t tag) {
    asm volatile("{\n.reg .pred p;\nsetp.ne.u32 p, %0, 0;\n@p st.relaxed.gpu.global.v2.b32 [%1], {%2,%3};\n}"
                 ::"r"(on), "l"(p), "r"(tagged(a, tag)), "r"(tagged(b, tag)) : "memory");
}
__device__ __forceinline__ void get4(uint32_t on, uint4& v, const uint32_t* p) {
    asm volatile("{\n.reg .pred p;\nsetp.ne.u32 p, %5, 0;\n@p ld.relaxed.gpu.global.v4.b32 {%0,%1,%2,%3}, [%4];\n}"
                 : "+r"(v.x), "+r"(v.y), "+r"(v.z), "+r"(v.w) : "l"(p), "r"(on) : "memory");
}
__device__ __forceinline__ uint32_t stale(const uint4& v, uint32_t tag) {
    return ((v.x ^ tag) | (v.y ^ tag) | (v.z ^ tag) | (v.w ^ tag)) & 3u;
}

__device__ __forceinline__ void layernorm_row(const uint4& u0, const uint4& u1, int lane, uint32_t xn_row) {
    const uint32_t u[8] = {u0.x, u0.y, u0.z, u0.w, u1.x, u1.y, u1.z, u1.w};
    float v[16], sum = 0.f;
#pragma unroll
    for (int i = 0; i < 8; i++) { v[2 * i] = bf_lo(u[i]); v[2 * i + 1] = bf_hi(u[i]); sum += v[2 * i] + v[2 * i + 1]; }
#pragma unroll
    for (int o = 16; o > 0; o >>= 1) sum += __shfl_xor_sync(~0u, sum, o);
    const float mean = sum * (1.f / DM);
    float sq = 0.f;
#pragma unroll
    for (int i = 0; i < 16; i++) sq += (v[i] - mean) * (v[i] - mean);
#pragma unroll
    for (int o = 16; o > 0; o >>= 1) sq += __shfl_xor_sync(~0u, sq, o);
    const float mean_b = round_bf16(mean);
    const float inv = rcp(round_bf16(sqrt_approx(round_bf16(round_bf16(sq * (1.f / DM)) + 1e-5f))));
    uint32_t r[8];
#pragma unroll
    for (int i = 0; i < 8; i++) r[i] = pack_bf16(round_bf16(v[2 * i] - mean_b) * inv, round_bf16(v[2 * i + 1] - mean_b) * inv);
    asm volatile("st.shared.v4.b32 [%0], {%1,%2,%3,%4};" ::"r"(xn_row + lane * 16), "r"(r[0]), "r"(r[1]), "r"(r[2]), "r"(r[3]) : "memory");
    asm volatile("st.shared.v4.b32 [%0], {%1,%2,%3,%4};" ::"r"(xn_row + 512 + lane * 16), "r"(r[4]), "r"(r[5]), "r"(r[6]), "r"(r[7]) : "memory");
}

__global__ void __launch_bounds__(N_THREADS, 1)
decode_kernel(const __grid_constant__ Maps maps, const __nv_bfloat16* __restrict__ x, __nv_bfloat16* __restrict__ out) {
    extern __shared__ __align__(1024) unsigned char smem_raw[];
    const uint32_t sm = ((uint32_t)__cvta_generic_to_shared(smem_raw) + 1023u) & ~1023u;
    const uint32_t bar_wq = sm + OFF_BAR, bar_full = bar_wq + 16, bar_wt = bar_full + 8 * NSLOT, bar_empty = bar_wt + 24;
    const int tid = threadIdx.x, w = tid >> 5, lane = tid & 31;
    const int cta = blockIdx.x;
    const bool att = cta < N_ATT;

    const int bar_first = att ? 0 : 2;

    if (w == 8) {
        if (lane == 0) {
#pragma unroll
            for (int i = 0; i < 3; i++) mbar_init(bar_wq + 8 * (bar_first + i), 1);
            asm volatile("fence.proxy.async.shared::cta;" ::: "memory");
#pragma unroll
            for (int i = 0; i < 3; i++) {
                const uint32_t bar = bar_wq + 8 * (bar_first + i);
                const bool wq = att && i < 2;
                mbar_expect_tx(bar, STAGE);
                tma_load(wq ? sm + OFF_W + i * 16384 : att ? sm : sm + i * STAGE, &maps.m[wq ? MAP_WQ : att ? MAP_K : MAP_WG],
                         wq ? cta * 32 : att ? 0 : (cta - N_ATT) * 448, wq ? i * 256 : att ? cta * 2048 : i * 128, bar);
            }
            PROBE_AT(8, 13);
        }
        __syncwarp();
        asm volatile("bar.sync 2, 64;" ::: "memory");
        if (lane != 0) return;
        const int n_ring = att ? KV_ITEMS : FFN_ITEMS;
        int landed = att ? -2 : 0, slot = landed + 3, lslot = 0;
        uint32_t phase = 1, lphase = 0;
        auto count_landed = [&]() {
            if (landed >= 0) {
                if (++lslot == NSLOT) { lslot = 0; lphase ^= 1; }
                if (att) asm volatile("red.relaxed.gpu.global.add.u32 [%0], 1;" ::"l"(&g_progress) : "memory");
            }
            if ((landed + 2) % 8 == 1) PROBE_AT(8, 14 + (landed + 2) / 8);
            landed++;
        };
#pragma unroll 1
        for (int n = slot; n < n_ring; n++) {
            int win = WIN_FFN;
            if (att) {
                const int lead = N_ATT * landed - (int)lds32(sm + OFF_CTL);
                win = WIN_BODY + (lead < -LAG_1) + (lead < -LAG_2) - (lead > LEAD_1);
                if (n < HEAD_ITEMS) win = WIN_HEAD;
                if (n >= KV_ITEMS - TAIL_ITEMS) win = WIN_TAIL;
            }
#pragma unroll 1
            while (landed <= n - win || (landed < n && mbar_test(bar_full + 8 * (landed < 0 ? landed : lslot), lphase))) {
                mbar_wait(bar_full + 8 * (landed < 0 ? landed : lslot), lphase);
                count_landed();
            }
            mbar_wait(bar_empty + 8 * slot, phase);
            const uint32_t bar = bar_full + 8 * slot;
            mbar_expect_tx(bar, STAGE);
            tma_load(sm + slot * STAGE, &maps.m[att ? MAP_K + ((n >> 1) & 1) : MAP_WG + ((n >> 2) & 1)],
                     att ? 0 : (cta - N_ATT) * 448 + (n >> 3) * 64,
                     att ? cta * 2048 + (n >> 2) * 128 + (n & 1) * 64 : (n & 3) * 128, bar);
            if (++slot == NSLOT) { slot = 0; phase ^= 1; }
        }
        if (att) {
            uint32_t spins = 0;
            bool gated = true;
#pragma unroll 1
            while (gated || landed < KV_ITEMS) {
                if (landed < KV_ITEMS && mbar_test(bar_full + 8 * lslot, lphase)) count_landed();
                if (gated && (int)lds32(sm + OFF_CTL) >= N_ATT * KV_ITEMS - GATE_LEFT) {
                    gated = false;
                    PROBE_AT(8, 23);
#pragma unroll 1
                    for (int i = 0; i < 3; i++) {
                        mbar_expect_tx(bar_wt + 8 * i, i ? 16384 : WD_ROWS * 128);
                        tma_load(sm + OFF_W + (i ? (i - 1) * 16384 : 32768), &maps.m[i ? MAP_WO : MAP_WD], (cta & 7) * 64,
                                 i ? (cta >> 3) * 256 + (i - 1) * 128 : (cta >> 3) * WD_ROWS, bar_wt + 8 * i);
                    }
                    sts32(sm + OFF_CTL + 4, 1);
                }
                if (++spins > SPIN_LIMIT) __trap();
            }
        }
        return;
    }
    if (w == 9) {
        if (lane == 0) {
#pragma unroll
            for (int i = 0; i < 2 * NSLOT + 5; i++)
                if (i >= 5 || (att ? i >= 3 : i < 2)) mbar_init(bar_wq + 8 * i, i < NSLOT + 5 ? 1 : att ? 4 : 8);
            sts64(sm + OFF_CTL, 0, 0);
            asm volatile("fence.proxy.async.shared::cta;" ::: "memory");
        }
        __syncwarp();
        asm volatile("bar.arrive 2, 64;" ::: "memory");
        asm volatile("bar.arrive 0, 288;" ::: "memory");
        if (lane == 0 && att) {
            uint32_t base, spins = 0;
            asm volatile("ld.relaxed.gpu.global.b32 %0, [%1];" : "=r"(base) : "l"(g_epoch + cta) : "memory");
            base *= N_ATT * KV_ITEMS;
            while (!lds32(sm + OFF_CTL + 4) && ++spins < SPIN_LIMIT) {
                uint32_t v;
                asm volatile("ld.relaxed.gpu.global.b32 %0, [%1];" : "=r"(v) : "l"(&g_progress) : "memory");
                sts32(sm + OFF_CTL, v - base);
            }
        }
        return;
    }

    const uint4* xr = reinterpret_cast<const uint4*>(x + w * DM);
    const uint4 xa = __ldg(xr + lane), xb = __ldg(xr + 32 + lane);
    uint32_t epoch;
    asm volatile("ld.relaxed.gpu.global.b32 %0, [%1];" : "=r"(epoch) : "l"(g_epoch + cta) : "memory");
    const int g = lane >> 2, t = lane & 3;
    const int out_idx = (lane & 7) * DM + cta * 4 + (lane >> 3);
    float x_res = 0.f;
    if (att && w == 0) x_res = __bfloat162float(__ldg(x + out_idx));
    layernorm_row(xa, xb, lane, sm + OFF_XN + w * XN_STRIDE);
    epoch += 1;
    const uint32_t tag = epoch & 3u;
    asm volatile("bar.sync 0, 288;" ::: "memory");
    PROBE_AT(0, 1);
    const uint32_t xn_addr = sm + OFF_XN + (lane & 7) * XN_STRIDE + (lane >> 3) * 16;

    if (!att) {
        int slot = 0;
        uint32_t phase = 0;
        const uint32_t b_off = lane * 128 + ((w ^ (lane & 7)) << 4);
        float acc[2][4] = {}, gate0 = 0.f, gate1 = 0.f;
#pragma unroll 1
        for (int n = 0; n < FFN_ITEMS; n++) {
            mbar_wait(bar_full + 8 * slot, phase);
            const uint32_t base = sm + slot * STAGE + b_off;
#pragma unroll
            for (int k = 0; k < 4; k++) {
                uint32_t a[4], b[4];
                ldsm4(a, xn_addr + (n & 3) * 256 + k * 64);
                ldsm4t(b, base + k * 4096);
                mma(acc[0], a[0], 0, a[1], 0, b[0], b[1]);
                mma(acc[1], a[2], 0, a[3], 0, b[2], b[3]);
            }
            __syncwarp();
            if (lane == 0) mbar_arrive(bar_empty + 8 * slot);
            if (++slot == NSLOT) { slot = 0; phase ^= 1; }
            if ((n & 3) == 3) {
                const float r0 = round_bf16(acc[0][0] + acc[1][0]), r1 = round_bf16(acc[0][1] + acc[1][1]);
                if (n & 4) put_pair(g_h + g * (FF / 2) + (cta - N_ATT) * 224 + (n >> 3) * 32 + w * 4 + t, pack_bf16(gate0 * r0, gate1 * r1), epoch);
                gate0 = round_bf16(sigmoid(r0));
                gate1 = round_bf16(sigmoid(r1));
                acc[0][0] = acc[0][1] = acc[1][0] = acc[1][1] = 0.f;
            }
        }
        if (tid == 0) g_epoch[cta] = epoch;
        PROBE_AT(0, 2);
        PROBE_DUMP();
        return;
    }

    const int batch = cta >> 4, hkv = (cta >> 1) & 7, half = cta & 1;

    if (w < 4) {
        float acc[2][4] = {};
        const uint32_t b_addr = sm + OFF_W + lane * 64 + ((w ^ ((lane >> 1) & 3)) << 4);
#pragma unroll 1
        for (int kh = 0; kh < 4; kh++) {
            mbar_wait(bar_wq + (kh >> 1) * 8, 0);
#pragma unroll
            for (int k = 0; k < 4; k++) {
                uint32_t a[4], b[4];
                ldsm4(a, xn_addr + kh * 256 + k * 64);
                ldsm4t(b, b_addr + kh * 8192 + k * 2048);
                mma(acc[0], a[0], 0, a[1], 0, b[0], b[1]);
                mma(acc[1], a[2], 0, a[3], 0, b[2], b[3]);
            }
        }
        put_pair(g_q + g * 2048 + cta * 16 + w * 4 + t, pack_bf16(acc[0][0] + acc[1][0], acc[0][1] + acc[1][1]), epoch);
    }
    PROBE_AT(0, 2);

    float o[8][4] = {};
    float m0 = -INFINITY, m1 = -INFINITY;
    const int sw = lane & 7;
    const int k_sel = lane >> 4, v_sel = (lane >> 3) & 1;
    const int ks = cta >> 3;
    uint32_t* const opart_dst = g_opart + (((hkv * 4 + (tid & 1) * 2) * 8 + batch) * 2 + half) * 128 + (tid >> 1);
    uint32_t* const stat_dst = g_stat + (((hkv * 4 + (t & 1) * 2) * 8 + batch) * 2 + half) * 2;
    uint32_t* const part_dst = g_part + (((w >> 2) * 16 + ks) * DM + (cta & 7) * 64 + (w & 3) * 16 + g) * 8 + t * 2;
    const unsigned long long* const h_src = g_h + w * (FF / 2) + ks * (WD_ROWS / 2) + lane;
    unsigned long long h0 = (unsigned long long)epoch << 32, h1 = h0;

    uint32_t live;
    asm volatile("mov.u32 %0, %1;" : "=r"(live) : "n"(1 - WARM));
#pragma unroll 1
    for (;; live = 1) {
        if (live) {
            sts32(sm + OFF_Q + (tid >> 6) * 272 + (tid & 63) * 4, get_pair((unsigned long long)~epoch << 32, g_q + batch * 2048 + hkv * 256 + tid, epoch));
            consumer_sync();
            uint32_t qf[8][2];
#pragma unroll
            for (int j = 0; j < 8; j++) {
                const uint32_t a = sm + OFF_Q + (g & 3) * 272 + j * 32 + t * 4;
                qf[j][0] = g < 4 ? lds32(a) : 0u;
                qf[j][1] = g < 4 ? lds32(a + 16) : 0u;
            }
            PROBE_AT(0, 3);

            const uint32_t k_off = ((w & 3) * 16 + sw + v_sel * 8) * 128;
            const uint32_t v_off = ((w & 3) * 16 + sw + k_sel * 8) * 128;
            float l0 = 0.f, l1 = 0.f;
            int slot = w >> 2;
            uint32_t phase = 0;
#pragma unroll 1
            for (int it = 0; it < N_STEPS; it++) {
                mbar_wait(bar_full + 8 * slot, phase);
                float s[2][4] = {};
                {
                    const uint32_t base = sm + slot * STAGE + k_off;
#pragma unroll
                    for (int j = 0; j < 8; j++) {
                        uint32_t a[4];
                        ldsm4(a, base + (j >> 2) * 8192 + ((((j & 3) * 2 + k_sel) ^ sw) << 4));
                        mma(s[j & 1], a[0], a[1], a[2], a[3], qf[j][0], qf[j][1]);
                    }
                }
                __syncwarp();
                if (lane == 0) mbar_arrive(bar_empty + 8 * slot);
                slot += 2;
                if (slot >= NSLOT) { slot -= NSLOT; phase ^= 1; }

                uint32_t sa = pack_bf16(s[0][0] + s[1][0], s[0][1] + s[1][1]);
                uint32_t sb = pack_bf16(s[0][2] + s[1][2], s[0][3] + s[1][3]);
                sa = pack_bf16(bf_lo(sa) * QK_SCALE, bf_hi(sa) * QK_SCALE);
                sb = pack_bf16(bf_lo(sb) * QK_SCALE, bf_hi(sb) * QK_SCALE);
                uint32_t mx = max_bf16x2(sa, sb);
                mx = max_bf16x2(mx, __shfl_xor_sync(~0u, mx, 4));
                mx = max_bf16x2(mx, __shfl_xor_sync(~0u, mx, 8));
                mx = max_bf16x2(mx, __shfl_xor_sync(~0u, mx, 16));
                float n0 = fmaxf(m0, bf_lo(mx)), n1 = fmaxf(m1, bf_hi(mx));
                const bool cta_wide = it == 0 || it == N_STEPS - 1;
                if (cta_wide) {
                    sts64_if(lane < 2, sm + OFF_STAT + w * 16 + t * 8, n0, n1);
                    consumer_sync();
#pragma unroll
                    for (int i = 0; i < 8; i++) {
                        const float2 v = lds64f(sm + OFF_STAT + i * 16 + (t & 1) * 8);
                        if (t < 2) { n0 = fmaxf(n0, v.x); n1 = fmaxf(n1, v.y); }
                    }
                }
                if (__any_sync(~0u, n0 != m0 || n1 != m1)) {
                    const float c0 = ex2((m0 - n0) * LOG2E), c1 = ex2((m1 - n1) * LOG2E);
                    l0 *= c0;
                    l1 *= c1;
#pragma unroll
                    for (int i = 0; i < 8; i++) { o[i][0] *= c0; o[i][1] *= c1; o[i][2] *= c0; o[i][3] *= c1; }
                    m0 = n0;
                    m1 = n1;
                }
                const float p0 = ex2((bf_lo(sa) - m0) * LOG2E), p1 = ex2((bf_hi(sa) - m1) * LOG2E);
                const float p2 = ex2((bf_lo(sb) - m0) * LOG2E), p3 = ex2((bf_hi(sb) - m1) * LOG2E);
                l0 += p0 + p2;
                l1 += p1 + p3;
                const uint32_t pb0 = transpose8x8(pack_bf16(p0, p1)), pb1 = transpose8x8(pack_bf16(p2, p3));
                if (cta_wide) {
                    float r0 = l0, r1 = l1;
#pragma unroll
                    for (int off = 4; off < 32; off <<= 1) {
                        r0 += __shfl_xor_sync(~0u, r0, off);
                        r1 += __shfl_xor_sync(~0u, r1, off);
                    }
                    sts64_if(lane < 2, sm + OFF_STAT + 128 + w * 16 + t * 8, r0, r1);
                    PROBE_AT(4, 4);
                }

                if (it == MARK_STEP) {
                    const uint32_t none = tag ^ 2u;
                    put1(1, opart_dst, 0.f, none);
                    put1(1, opart_dst + 8 * 2 * 128, 0.f, none);
                    put2(tid < 2, stat_dst, 0.f, 0.f, none);
                    put2(tid < 2, stat_dst + 8 * 4, 0.f, 0.f, none);
                    put2(1, part_dst, 0.f, 0.f, none);
                    put2(1, part_dst + 64, 0.f, 0.f, none);
                    ld_pair(1, h0, h_src);
                    ld_pair(lane < WD_ROWS / 2 - 32, h1, h_src + 32);
                }

                mbar_wait(bar_full + 8 * slot, phase);
                PROBE_AT(4, 5);
                {
                    const uint32_t base = sm + slot * STAGE + v_off;
#pragma unroll
                    for (int i = 0; i < 8; i++) {
                        uint32_t a[4];
                        ldsm4t(a, base + (i >> 2) * 8192 + ((((i & 3) * 2 + v_sel) ^ sw) << 4));
                        mma(o[i], a[0], a[1], a[2], a[3], pb0, pb1);
                    }
                }
                __syncwarp();
                if (lane == 0) mbar_arrive(bar_empty + 8 * slot);
                slot += 2;
                if (slot >= NSLOT) { slot -= NSLOT; phase ^= 1; }
            }
        }

        {
            constexpr int RED = ((KV_ITEMS - 4) % NSLOT) * STAGE;
            const uint32_t on = live && t < 2;
#pragma unroll
            for (int i = 0; i < 8; i++) {
                const uint32_t a = sm + RED + w * 2048 + (i * 16 + g) * 16 + t * 8;
                sts64_if(on, a, o[i][0], o[i][1]);
                sts64_if(on, a + 128, o[i][2], o[i][3]);
            }
            consumer_sync();
            float a0 = 0.f, a1 = 0.f, L0 = 0.f, L1 = 0.f;
#pragma unroll
            for (int i = 0; i < 8; i++) {
                const float2 v = lds64f(sm + RED + i * 2048 + tid * 8);
                a0 += v.x;
                a1 += v.y;
            }
            put1(live, opart_dst, a0, tag);
            put1(live, opart_dst + 8 * 2 * 128, a1, tag);
            if (w == 0) {
#pragma unroll
                for (int i = 0; i < 8; i++) {
                    const float2 v = lds64f(sm + OFF_STAT + 128 + i * 16 + (t & 1) * 8);
                    L0 += v.x;
                    L1 += v.y;
                }
                put2(live && lane < 2, stat_dst, m0, L0, tag);
                put2(live && lane < 2, stat_dst + 8 * 4, m1, L1, tag);
            }
        }
        PROBE_AT(4, 6);

        {
            const uint4 ready = make_uint4(tag, tag, tag, tag);
            uint4 st[2] = {ready, ready}, u[2][2] = {{ready, ready}, {ready, ready}};
            const uint32_t* src = g_opart + (ks * 16 + w) * 256 + lane * 4;
            uint32_t spins = 0, want_st = live, want_u = live, bulk = live;
            do {
                get4(want_st, st[0], g_stat + (ks * 16 + w) * 4);
                get4(want_st, st[1], g_stat + (ks * 16 + 8 + w) * 4);
#pragma unroll
                for (int i = 0; i < 4; i++) get4(bulk, u[i >> 1][i & 1], src + (i >> 1) * 2048 + (i & 1) * 128);
                want_st = stale(st[0], tag) | stale(st[1], tag);
                want_u = stale(u[0][0], tag) | stale(u[0][1], tag) | stale(u[1][0], tag) | stale(u[1][1], tag);
                bulk = want_u && !want_st;
                if (++spins > SPIN_LIMIT) __trap();
            } while (want_st | want_u);
            PROBE_AT(4, 7);
            sts32(sm + OFF_H + w * H_STRIDE + lane * 4, get_pair(h0, h_src, epoch));
            const uint32_t h2 = get_pair(h1, h_src + 32, epoch);
            if (lane < WD_ROWS / 2 - 32) sts32(sm + OFF_H + w * H_STRIDE + 128 + lane * 4, h2);
#pragma unroll
            for (int i = 0; i < 2; i++) {
                const float ma = __uint_as_float(st[i].x & ~3u), mb = __uint_as_float(st[i].z & ~3u);
                const float mm = fmaxf(ma, mb);
                float wa = ex2((ma - mm) * LOG2E), wb = ex2((mb - mm) * LOG2E);
                const float inv = rcp(wa * __uint_as_float(st[i].y) + wb * __uint_as_float(st[i].w));
                wa *= inv;
                wb *= inv;
                const uint4 &ua = u[i][0], &ub = u[i][1];
                sts64(sm + OFF_O + w * O_STRIDE + i * 256 + lane * 8,
                      pack_bf16(wa * __uint_as_float(ua.x) + wb * __uint_as_float(ub.x), wa * __uint_as_float(ua.y) + wb * __uint_as_float(ub.y)),
                      pack_bf16(wa * __uint_as_float(ua.z) + wb * __uint_as_float(ub.z), wa * __uint_as_float(ua.w) + wb * __uint_as_float(ub.w)));
            }
        }
        consumer_sync();
        PROBE_AT(4, 8);
        PROBE_AT(0, 26);
        {
            const uint32_t a_off = sm + OFF_W + (sw + k_sel * 8) * 128 + ((((w & 3) * 2 + v_sel) ^ sw) << 4);
            float c[2][4] = {};
            if (w < 4) {
                uint32_t b[8][4];
#pragma unroll
                for (int k = 0; k < 8; k++) ldsm4(b[k], sm + OFF_O + sw * O_STRIDE + (lane >> 3) * 16 + k * 64);
#pragma unroll
                for (int k = 0; k < 16; k++) {
                    if (k % 8 == 0 && live) mbar_wait(bar_wt + 8 + k, 0);
                    if (k == 8) PROBE_AT(0, 9);
                    if (k == 0) PROBE_AT(0, 27);
                    uint32_t a[4];
                    ldsm4t(a, a_off + k * 2048);
                    mma(c[k & 1], a[0], a[1], a[2], a[3], b[k >> 1][(k & 1) * 2], b[k >> 1][(k & 1) * 2 + 1]);
                }
            } else {
                uint32_t b[4][4];
#pragma unroll
                for (int k = 0; k < 3; k++) ldsm4(b[k], sm + OFF_H + sw * H_STRIDE + (lane >> 3) * 16 + k * 64);
                ldsm2(b[3][0], b[3][1], sm + OFF_H + sw * H_STRIDE + v_sel * 16 + 192);
                if (live) mbar_wait(bar_wt, 0);
#pragma unroll
                for (int k = 0; k < 7; k++) {
                    uint32_t a[4];
                    ldsm4t(a, a_off + 32768 + k * 2048);
                    mma(c[k & 1], a[0], a[1], a[2], a[3], b[k >> 1][(k & 1) * 2], b[k >> 1][(k & 1) * 2 + 1]);
                }
            }
            put2(live, part_dst, c[0][0] + c[1][0], c[0][1] + c[1][1], tag);
            put2(live, part_dst + 64, c[0][2] + c[1][2], c[0][3] + c[1][3], tag);
        }
        PROBE_AT(0, 10);

        {
            const uint32_t* src = g_part + ((w * 4 + (lane >> 3)) * DM + cta * 4) * 8 + (lane & 7) * 4;
            uint4 u = make_uint4(tag, tag, tag, tag);
            uint32_t pending = live, spins = 0;
            do {
                get4(pending, u, src);
                pending = stale(u, tag);
                if (++spins > SPIN_LIMIT) __trap();
            } while (pending);
            __syncwarp();
            PROBE_AT(0, 11);
            const bool up = lane & 16, b3 = lane & 8;
            const float a0 = __uint_as_float(up ? u.z : u.x) + __shfl_xor_sync(~0u, __uint_as_float(up ? u.x : u.z), 16);
            const float a1 = __uint_as_float(up ? u.w : u.y) + __shfl_xor_sync(~0u, __uint_as_float(up ? u.y : u.w), 16);
            const float r = (b3 ? a1 : a0) + __shfl_xor_sync(~0u, b3 ? a0 : a1, 8);
            sts32(sm + OFF_FIN + w * 128 + ((lane & 7) * 4 + (lane >> 4) * 2 + ((lane >> 3) & 1)) * 4, __float_as_uint(r));
            consumer_sync();
            if (w == 0) {
                float v[8];
#pragma unroll
                for (int i = 0; i < 8; i++) v[i] = __uint_as_float(lds32(sm + OFF_FIN + i * 128 + lane * 4));
                const float sv = round_bf16((v[0] + v[1]) + (v[2] + v[3])), d = round_bf16((v[4] + v[5]) + (v[6] + v[7]));
                const uint32_t res = pack_bf16(x_res + round_bf16(sv * round_bf16(d * sigmoid(d))), 0.f);
                asm volatile("{\n.reg .pred p;\n.reg .b16 lo, hi;\nsetp.ne.u32 p, %0, 0;\nmov.b32 {lo, hi}, %2;\n@p st.global.b16 [%1], lo;\n}"
                             ::"r"(live), "l"(out + out_idx), "r"(res) : "memory");
                if (live && lane == 0) g_epoch[cta] = epoch;
                PROBE_AT(0, 12);
            }
        }
        if (live) break;
    }
    PROBE_DUMP();
}

using EncodeFn = CUresult (*)(CUtensorMap*, CUtensorMapDataType, cuuint32_t, void*, const cuuint64_t*, const cuuint64_t*,
                              const cuuint32_t*, const cuuint32_t*, CUtensorMapInterleave, CUtensorMapSwizzle,
                              CUtensorMapL2promotion, CUtensorMapFloatOOBfill);

void encode(EncodeFn fn, CUtensorMap* m, void* p, const cuuint64_t (&dims)[3], const cuuint64_t (&strides)[2],
            const cuuint32_t (&box)[3], CUtensorMapSwizzle swizzle, CUtensorMapL2promotion promotion) {
    const cuuint32_t elem[3] = {1, 1, 1};
    fn(m, CU_TENSOR_MAP_DATA_TYPE_BFLOAT16, 3, p, dims, strides, box, elem, CU_TENSOR_MAP_INTERLEAVE_NONE, swizzle,
       promotion, CU_TENSOR_MAP_FLOAT_OOB_FILL_NONE);
}

void encode_matrix(EncodeFn fn, CUtensorMap* m, void* p, cuuint64_t rows, cuuint64_t cols, cuuint32_t box_rows,
                   cuuint32_t box_cols, CUtensorMapSwizzle swizzle,
                   CUtensorMapL2promotion promotion = CU_TENSOR_MAP_L2_PROMOTION_NONE) {
    encode(fn, m, p, {cols, rows, 1}, {cols * 2, rows * cols * 2}, {box_cols, box_rows, 1}, swizzle, promotion);
}

void encode_cache(EncodeFn fn, CUtensorMap* m, void* p) {
    encode(fn, m, p, {64, 8 * 8 * 4096, 2}, {256, 128}, {64, 64, 2}, CU_TENSOR_MAP_SWIZZLE_128B, CU_TENSOR_MAP_L2_PROMOTION_NONE);
}

}

extern "C" void kernel_launch(void* const* d_in, const int* in_sizes, int n_in, void* d_out, int out_size) {
    (void)in_sizes; (void)n_in; (void)out_size;
    static EncodeFn fn = nullptr;
    if (!fn) {
        cudaDriverEntryPointQueryResult status;
        cudaGetDriverEntryPoint("cuTensorMapEncodeTiled", (void**)&fn, cudaEnableDefault, &status);
        cudaFuncSetAttribute(decode_kernel, cudaFuncAttributeMaxDynamicSharedMemorySize, SMEM_BYTES);
    }
    Maps maps;
    encode_cache(fn, &maps.m[MAP_K], d_in[1]);
    encode_cache(fn, &maps.m[MAP_V], d_in[2]);
    encode_matrix(fn, &maps.m[MAP_WQ], d_in[3], DM, 4096, 256, 32, CU_TENSOR_MAP_SWIZZLE_64B, WQ_PROMO);
    encode_matrix(fn, &maps.m[MAP_WO], d_in[4], 4096, DM, 128, 64, CU_TENSOR_MAP_SWIZZLE_128B);
    encode_matrix(fn, &maps.m[MAP_WG], d_in[6], DM, FF, 128, 64, CU_TENSOR_MAP_SWIZZLE_128B);
    encode_matrix(fn, &maps.m[MAP_WU], d_in[7], DM, FF, 128, 64, CU_TENSOR_MAP_SWIZZLE_128B);
    encode_matrix(fn, &maps.m[MAP_WD], d_in[8], FF, DM, WD_ROWS, 64, CU_TENSOR_MAP_SWIZZLE_128B);
    decode_kernel<<<GRID, N_THREADS, SMEM_BYTES>>>(maps, (const __nv_bfloat16*)d_in[0], (__nv_bfloat16*)d_out);
}
```

```cpp
#include <cuda.h>
#include <cuda_bf16.h>
#include <cuda_runtime.h>
#include <stdint.h>

namespace {

constexpr int DM = 512, FF = 1792;
constexpr int N_ATT = 128, N_FFN = 4, GRID = N_ATT + N_FFN;
constexpr int N_THREADS = 320;
constexpr int STAGE = 16384, NSLOT = 10;
constexpr int KV_ITEMS = 64;
constexpr int LAST = 14;
constexpr int FF_SLICE = FF / N_FFN;
constexpr int GU_ITEMS = 2 * DM / 16;
constexpr int FFN_ITEMS = GU_ITEMS + FF_SLICE / 16;

constexpr int WIN_HEAD = 3, HEAD_ITEMS = 6, WIN_BODY = 4, WIN_FFN = 10;
constexpr int LAG_1 = 48, LAG_2 = 128, LEAD_1 = 160;
constexpr int TAIL_ITEMS = 8, WIN_TAIL = 10, WIN_TAIL_LEAD = 5, TAIL_LEAD = 192;
constexpr int GATE_LEFT = 600;
constexpr int RESET_STEP = 10;

constexpr int OFF_W = NSLOT * STAGE;
constexpr int H_STRIDE = 912;
constexpr int OFF_XN = OFF_W + 32768;
constexpr int XN_STRIDE = 1040;
constexpr int OFF_Q = OFF_XN + 8 * XN_STRIDE;
constexpr int OFF_O = OFF_Q + 4 * 272;
constexpr int O_STRIDE = 272;
constexpr int OFF_STAT = OFF_O + 8 * O_STRIDE;
constexpr int OFF_P = OFF_STAT + 256;
constexpr int OFF_BAR = OFF_P + 4096;
constexpr int OFF_CTL = OFF_BAR + 240;
constexpr int SMEM_BYTES = OFF_BAR + 256 + 1024;

constexpr float LOG2E = 1.4426950408889634f;
constexpr float QK_SCALE = 0.08838834764831845f;
constexpr uint32_t SPIN_LIMIT = 1u << 24;

enum { MAP_K, MAP_V, MAP_WQ, MAP_WG, MAP_WU, MAP_WD, MAP_WO, N_MAPS };
struct Maps { CUtensorMap m[N_MAPS]; };

__device__ uint32_t g_epoch[GRID];
__device__ uint32_t g_progress;
__device__ unsigned long long g_q[8 * 2048];
__device__ __align__(128) uint32_t g_opart[32 * 8 * 2 * 128];
__device__ __align__(128) uint32_t g_stat[32 * 8 * 4];
__device__ __align__(128) uint32_t g_part[32 * DM * 8];
__device__ __align__(128) uint32_t g_down[N_FFN * DM * 8];

__device__ __forceinline__ void mbar_init(uint32_t bar, uint32_t count) {
    asm volatile("mbarrier.init.shared::cta.b64 [%0], %1;" ::"r"(bar), "r"(count) : "memory");
}
__device__ __forceinline__ void mbar_expect_tx(uint32_t bar, uint32_t bytes) {
    asm volatile("mbarrier.arrive.expect_tx.shared::cta.b64 _, [%0], %1;" ::"r"(bar), "r"(bytes) : "memory");
}
__device__ __forceinline__ void mbar_arrive(uint32_t bar) {
    asm volatile("mbarrier.arrive.shared::cta.b64 _, [%0];" ::"r"(bar) : "memory");
}
__device__ __forceinline__ uint32_t mbar_test(uint32_t bar, uint32_t parity) {
    uint32_t ok;
    asm volatile("{\n.reg .pred p;\nmbarrier.test_wait.parity.shared::cta.b64 p, [%1], %2;\nselp.u32 %0, 1, 0, p;\n}"
                 : "=r"(ok) : "r"(bar), "r"(parity) : "memory");
    return ok;
}
__device__ __forceinline__ void mbar_wait(uint32_t bar, uint32_t parity) {
    uint32_t ok, spins = 0;
    do {
        asm volatile("{\n.reg .pred p;\nmbarrier.try_wait.parity.shared::cta.b64 p, [%1], %2;\nselp.u32 %0, 1, 0, p;\n}"
                     : "=r"(ok) : "r"(bar), "r"(parity) : "memory");
        if (++spins > SPIN_LIMIT) __trap();
    } while (!ok);
}
__device__ __forceinline__ void tma_load(uint32_t dst, const CUtensorMap* m, int row, int block, uint32_t bar) {
    asm volatile("{\n.reg .b64 policy;\ncreatepolicy.fractional.L2::evict_first.b64 policy, 1.0;\n"
                 "cp.async.bulk.tensor.3d.shared::cluster.global.mbarrier::complete_tx::bytes.L2::cache_hint [%0], [%1, {%3, %4, %5}], [%2], policy;\n}"
                 ::"r"(dst), "l"(m), "r"(bar), "r"(0), "r"(row), "r"(block) : "memory");
}
__device__ __forceinline__ void consumer_sync() { asm volatile("bar.sync 1, 256;" ::: "memory"); }
__device__ __forceinline__ void ldsm4(uint32_t (&r)[4], uint32_t addr) {
    asm volatile("ldmatrix.sync.aligned.m8n8.x4.shared.b16 {%0,%1,%2,%3}, [%4];"
                 : "=r"(r[0]), "=r"(r[1]), "=r"(r[2]), "=r"(r[3]) : "r"(addr) : "memory");
}
__device__ __forceinline__ void ldsm4t(uint32_t (&r)[4], uint32_t addr) {
    asm volatile("ldmatrix.sync.aligned.m8n8.x4.trans.shared.b16 {%0,%1,%2,%3}, [%4];"
                 : "=r"(r[0]), "=r"(r[1]), "=r"(r[2]), "=r"(r[3]) : "r"(addr) : "memory");
}
__device__ __forceinline__ void mma(float (&c)[4], uint32_t a0, uint32_t a1, uint32_t a2, uint32_t a3, uint32_t b0, uint32_t b1) {
    asm volatile("mma.sync.aligned.m16n8k16.row.col.f32.bf16.bf16.f32 {%0,%1,%2,%3}, {%4,%5,%6,%7}, {%8,%9}, {%0,%1,%2,%3};"
                 : "+f"(c[0]), "+f"(c[1]), "+f"(c[2]), "+f"(c[3])
                 : "r"(a0), "r"(a1), "r"(a2), "r"(a3), "r"(b0), "r"(b1));
}
__device__ __forceinline__ uint32_t transpose8x8(uint32_t a) {
    uint32_t d;
    asm volatile("movmatrix.sync.aligned.m8n8.trans.b16 %0, %1;" : "=r"(d) : "r"(a));
    return d;
}
__device__ __forceinline__ uint32_t pack_bf16(float lo, float hi) {
    uint32_t d;
    asm("cvt.rn.bf16x2.f32 %0, %1, %2;" : "=r"(d) : "f"(hi), "f"(lo));
    return d;
}
__device__ __forceinline__ float bf_lo(uint32_t v) { return __uint_as_float(v << 16); }
__device__ __forceinline__ float bf_hi(uint32_t v) { return __uint_as_float(v & 0xffff0000u); }
__device__ __forceinline__ float round_bf16(float v) { return bf_lo(pack_bf16(v, 0.f)); }
__device__ __forceinline__ uint32_t max_bf16x2(uint32_t a, uint32_t b) {
    uint32_t d;
    asm("max.bf16x2 %0, %1, %2;" : "=r"(d) : "r"(a), "r"(b));
    return d;
}
__device__ __forceinline__ float ex2(float x) {
    float y;
    asm("ex2.approx.ftz.f32 %0, %1;" : "=f"(y) : "f"(x));
    return y;
}
__device__ __forceinline__ float rcp(float x) {
    float y;
    asm("rcp.approx.ftz.f32 %0, %1;" : "=f"(y) : "f"(x));
    return y;
}
__device__ __forceinline__ float sqrt_approx(float x) {
    float y;
    asm("sqrt.approx.ftz.f32 %0, %1;" : "=f"(y) : "f"(x));
    return y;
}
__device__ __forceinline__ float sigmoid(float x) { return rcp(1.f + ex2(-x * LOG2E)); }
__device__ __forceinline__ void sts32(uint32_t addr, uint32_t v) { asm volatile("st.shared.b32 [%0], %1;" ::"r"(addr), "r"(v) : "memory"); }
__device__ __forceinline__ void sts64(uint32_t addr, uint32_t a, uint32_t b) { asm volatile("st.shared.v2.b32 [%0], {%1,%2};" ::"r"(addr), "r"(a), "r"(b) : "memory"); }
__device__ __forceinline__ uint32_t lds32(uint32_t addr) {
    uint32_t v;
    asm volatile("ld.shared.b32 %0, [%1];" : "=r"(v) : "r"(addr) : "memory");
    return v;
}
__device__ __forceinline__ uint2 lds64(uint32_t addr) {
    uint2 v;
    asm volatile("ld.shared.v2.b32 {%0,%1}, [%2];" : "=r"(v.x), "=r"(v.y) : "r"(addr) : "memory");
    return v;
}
__device__ __forceinline__ float2 lds64f(uint32_t addr) {
    float2 v;
    asm volatile("ld.shared.v2.f32 {%0,%1}, [%2];" : "=f"(v.x), "=f"(v.y) : "r"(addr) : "memory");
    return v;
}

__device__ __forceinline__ void sts64_if(uint32_t on, uint32_t addr, float a, float b) {
    asm volatile("{\n.reg .pred p;\nsetp.ne.u32 p, %0, 0;\n@p st.shared.v2.f32 [%1], {%2,%3};\n}" ::"r"(on), "r"(addr), "f"(a), "f"(b) : "memory");
}

__device__ __forceinline__ void put_pair(unsigned long long* p, uint32_t data, uint32_t epoch) {
    asm volatile("st.relaxed.gpu.global.b64 [%0], %1;" ::"l"(p), "l"(((unsigned long long)epoch << 32) | data) : "memory");
}
__device__ __forceinline__ void ld_pair(uint32_t on, unsigned long long& v, const unsigned long long* p) {
    asm volatile("{\n.reg .pred p;\nsetp.ne.u32 p, %2, 0;\n@p ld.relaxed.gpu.global.b64 %0, [%1];\n}" : "+l"(v) : "l"(p), "r"(on) : "memory");
}
__device__ __forceinline__ uint32_t get_pair(unsigned long long v, const unsigned long long* p, uint32_t epoch) {
    uint32_t spins = 0;
    while ((uint32_t)(v >> 32) != epoch) {
        ld_pair(1, v, p);
        if (++spins > SPIN_LIMIT) __trap();
    }
    return (uint32_t)v;
}
__device__ __forceinline__ uint32_t tagged(float v, uint32_t tag) { return (__float_as_uint(v) & ~3u) | tag; }
__device__ __forceinline__ void put1(uint32_t on, uint32_t* p, float a, uint32_t tag) {
    asm volatile("{\n.reg .pred p;\nsetp.ne.u32 p, %0, 0;\n@p st.relaxed.gpu.global.b32 [%1], %2;\n}" ::"r"(on), "l"(p), "r"(tagged(a, tag)) : "memory");
}
__device__ __forceinline__ void put2(uint32_t on, uint32_t* p, float a, float b, uint32_t tag) {
    asm volatile("{\n.reg .pred p;\nsetp.ne.u32 p, %0, 0;\n@p st.relaxed.gpu.global.v2.b32 [%1], {%2,%3};\n}"
                 ::"r"(on), "l"(p), "r"(tagged(a, tag)), "r"(tagged(b, tag)) : "memory");
}
__device__ __forceinline__ void get1(uint32_t on, uint32_t& v, const uint32_t* p) {
    asm volatile("{\n.reg .pred p;\nsetp.ne.u32 p, %2, 0;\n@p ld.relaxed.gpu.global.b32 %0, [%1];\n}" : "+r"(v) : "l"(p), "r"(on) : "memory");
}
__device__ __forceinline__ void get4(uint32_t on, uint4& v, const uint32_t* p) {
    asm volatile("{\n.reg .pred p;\nsetp.ne.u32 p, %5, 0;\n@p ld.relaxed.gpu.global.v4.b32 {%0,%1,%2,%3}, [%4];\n}"
                 : "+r"(v.x), "+r"(v.y), "+r"(v.z), "+r"(v.w) : "l"(p), "r"(on) : "memory");
}
__device__ __forceinline__ uint32_t stale(const uint4& v, uint32_t tag) {
    return ((v.x ^ tag) | (v.y ^ tag) | (v.z ^ tag) | (v.w ^ tag)) & 3u;
}

__device__ __forceinline__ void layernorm_row(const uint4& u0, const uint4& u1, int lane, uint32_t xn_row) {
    const uint32_t u[8] = {u0.x, u0.y, u0.z, u0.w, u1.x, u1.y, u1.z, u1.w};
    float v[16], sum = 0.f;
#pragma unroll
    for (int i = 0; i < 8; i++) { v[2 * i] = bf_lo(u[i]); v[2 * i + 1] = bf_hi(u[i]); sum += v[2 * i] + v[2 * i + 1]; }
#pragma unroll
    for (int o = 16; o > 0; o >>= 1) sum += __shfl_xor_sync(~0u, sum, o);
    const float mean = sum * (1.f / DM);
    float sq = 0.f;
#pragma unroll
    for (int i = 0; i < 16; i++) sq += (v[i] - mean) * (v[i] - mean);
#pragma unroll
    for (int o = 16; o > 0; o >>= 1) sq += __shfl_xor_sync(~0u, sq, o);
    const float mean_b = round_bf16(mean);
    const float inv = rcp(round_bf16(sqrt_approx(round_bf16(round_bf16(sq * (1.f / DM)) + 1e-5f))));
    uint32_t r[8];
#pragma unroll
    for (int i = 0; i < 8; i++) r[i] = pack_bf16(round_bf16(v[2 * i] - mean_b) * inv, round_bf16(v[2 * i + 1] - mean_b) * inv);
    asm volatile("st.shared.v4.b32 [%0], {%1,%2,%3,%4};" ::"r"(xn_row + lane * 16), "r"(r[0]), "r"(r[1]), "r"(r[2]), "r"(r[3]) : "memory");
    asm volatile("st.shared.v4.b32 [%0], {%1,%2,%3,%4};" ::"r"(xn_row + 512 + lane * 16), "r"(r[4]), "r"(r[5]), "r"(r[6]), "r"(r[7]) : "memory");
}

__global__ void __launch_bounds__(N_THREADS, 1)
decode_kernel(const __grid_constant__ Maps maps, const __nv_bfloat16* __restrict__ x, __nv_bfloat16* __restrict__ out) {
    extern __shared__ __align__(1024) unsigned char smem_raw[];
    const uint32_t sm = ((uint32_t)__cvta_generic_to_shared(smem_raw) + 1023u) & ~1023u;
    const uint32_t bar_wq = sm + OFF_BAR, bar_full = bar_wq + 16, bar_wo = bar_full + 8 * NSLOT, bar_empty = bar_wo + 8;
    const int tid = threadIdx.x, w = tid >> 5, lane = tid & 31;
    const int cta = blockIdx.x;
    const bool att = cta < N_ATT;

    if (__builtin_expect(tid == 256 && att, 1)) {
#pragma unroll
        for (int i = 0; i < 3; i++) mbar_init(bar_wq + 8 * i, 1);
        asm volatile("fence.proxy.async.shared::cta;" ::: "memory");
#pragma unroll
        for (int i = 0; i < 2; i++) {
            mbar_expect_tx(bar_wq + 8 * i, STAGE);
            tma_load(sm + OFF_W + i * STAGE, &maps.m[MAP_WQ], i * 256, cta, bar_wq + 8 * i);
        }
        mbar_expect_tx(bar_full, STAGE);
        tma_load(sm, &maps.m[MAP_K], cta * 2048, 0, bar_full);
    }

    if (w == 8) {
        __syncwarp();
        asm volatile("bar.sync 2, 64;" ::: "memory");
        if (lane != 0) return;
        const int n_ring = att ? KV_ITEMS : FFN_ITEMS;
        int landed = att ? -2 : 0, slot = att ? 1 : 0, lslot = 0;
        uint32_t phase = 1, lphase = 0;
        auto count_landed = [&]() {
            if (landed >= 0) {
                if (++lslot == NSLOT) { lslot = 0; lphase ^= 1; }
                if (att) asm volatile("red.relaxed.gpu.global.add.u32 [%0], 1;" ::"l"(&g_progress) : "memory");
            }
            landed++;
        };
#pragma unroll 1
        for (int n = slot; n < n_ring; n++) {
            int win = WIN_FFN;
            if (att) {
                const int lead = N_ATT * landed - (int)lds32(sm + OFF_CTL);
                win = WIN_BODY + (lead < -LAG_1) + (lead < -LAG_2) - (lead > LEAD_1);
                if (n < HEAD_ITEMS) win = WIN_HEAD;
                if (n >= KV_ITEMS - TAIL_ITEMS) win = lead > TAIL_LEAD ? WIN_TAIL_LEAD : WIN_TAIL;
            }
#pragma unroll 1
            while (landed <= n - win || (landed < n && mbar_test(bar_full + 8 * (landed < 0 ? landed : lslot), lphase))) {
                mbar_wait(bar_full + 8 * (landed < 0 ? landed : lslot), lphase);
                count_landed();
            }
            mbar_wait(bar_empty + 8 * slot, phase);
            const uint32_t bar = bar_full + 8 * slot;
            mbar_expect_tx(bar, att || n >= GU_ITEMS ? STAGE : 32 * FF_SLICE);
            int map = MAP_K + ((n >> 1) & 1), row = cta * 2048 + (n >> 2) * 128 + (n & 1) * 64, block = 0;
            if (n >= 4 * LAST) {
                map = MAP_K + ((n >> 2) & 1);
                row = cta * 2048 + LAST * 128 + (n & 3) * 64;
            }
            if (!att) {
                const bool gu = n < GU_ITEMS;
                map = gu ? MAP_WG + (n & 1) : MAP_WD;
                row = gu ? (n >> 1) * 16 : (cta - N_ATT) * FF_SLICE + (n - GU_ITEMS) * 16;
                block = gu ? (cta - N_ATT) * (FF_SLICE / 64) : 0;
            }
            tma_load(sm + slot * STAGE, &maps.m[map], row, block, bar);
            if (++slot == NSLOT) { slot = 0; phase ^= 1; }
        }
        if (att) {
            uint32_t spins = 0;
            bool gated = true;
#pragma unroll 1
            while (gated || landed < KV_ITEMS) {
                if (landed < KV_ITEMS && mbar_test(bar_full + 8 * lslot, lphase)) count_landed();
                if (gated && (int)lds32(sm + OFF_CTL) >= N_ATT * KV_ITEMS - GATE_LEFT) {
                    gated = false;
                    mbar_expect_tx(bar_wo, 32768);
                    tma_load(sm + OFF_W, &maps.m[MAP_WO], (cta >> 2) * 128, (cta & 3) * 2, bar_wo);
                    sts32(sm + OFF_CTL + 4, 1);
                }
                if (++spins > SPIN_LIMIT) __trap();
            }
        }
        return;
    }
    if (w == 9) {
        if (lane == 0) {
#pragma unroll
            for (int i = 0; i < 2 * NSLOT + 3; i++)
                if (i >= 3 || !att) mbar_init(bar_wq + 8 * i, i < NSLOT + 3 ? 1 : att ? 4 : 8);
            sts64(sm + OFF_CTL, 0, 0);
            asm volatile("fence.proxy.async.shared::cta;" ::: "memory");
        }
        __syncwarp();
        asm volatile("bar.arrive 2, 64;" ::: "memory");
        asm volatile("bar.arrive 0, 288;" ::: "memory");
        if (lane == 0 && att) {
            uint32_t base, spins = 0;
            asm volatile("ld.relaxed.gpu.global.b32 %0, [%1];" : "=r"(base) : "l"(g_epoch + cta) : "memory");
            base *= N_ATT * KV_ITEMS;
            while (!lds32(sm + OFF_CTL + 4) && ++spins < SPIN_LIMIT) {
                uint32_t v;
                asm volatile("ld.relaxed.gpu.global.b32 %0, [%1];" : "=r"(v) : "l"(&g_progress) : "memory");
                sts32(sm + OFF_CTL, v - base);
            }
        }
        return;
    }

    const uint4* xr = reinterpret_cast<const uint4*>(x + w * DM);
    const uint4 xa = __ldg(xr + lane), xb = __ldg(xr + 32 + lane);
    uint32_t epoch;
    asm volatile("ld.relaxed.gpu.global.b32 %0, [%1];" : "=r"(epoch) : "l"(g_epoch + cta) : "memory");
    const int g = lane >> 2, t = lane & 3;
    const int out_batch = (cta & 3) * 2 + (lane & 1), out_col = (cta >> 2) * 16 + (lane >> 1);
    float x_res = 0.f;
    if (att && w == 0) x_res = __bfloat162float(__ldg(x + out_batch * DM + out_col));
    layernorm_row(xa, xb, lane, sm + OFF_XN + w * XN_STRIDE);
    epoch += 1;
    const uint32_t tag = epoch & 3u;
    asm volatile("bar.sync 0, 288;" ::: "memory");
    const uint32_t xn_addr = sm + OFF_XN + (lane & 7) * XN_STRIDE + (lane >> 3) * 16;
    const int sw = lane & 7;
    const int k_sel = lane >> 4, v_sel = (lane >> 3) & 1;

    if (!att) {
        int slot = 0;
        uint32_t phase = 0;
        float acc[2][7][4] = {};
#pragma unroll 1
        for (int k = 0; k < DM / 16; k++) {
            uint32_t a[4];
            ldsm4(a, xn_addr + k * 32);
#pragma unroll
            for (int u = 0; u < 2; u++) {
                mbar_wait(bar_full + 8 * slot, phase);
#pragma unroll
                for (int j = 0; j < 7; j += 2) {
                    uint32_t b[4];
                    ldsm4t(b, sm + slot * STAGE + j * 2048 + lane * 128 + ((w ^ sw) << 4));
                    mma(acc[u][j], a[0], 0, a[1], 0, b[0], b[1]);
                    if (j < 6) mma(acc[u][j + 1], a[0], 0, a[1], 0, b[2], b[3]);
                }
                __syncwarp();
                if (lane == 0) mbar_arrive(bar_empty + 8 * slot);
                if (++slot == NSLOT) { slot = 0; phase ^= 1; }
            }
        }
#pragma unroll
        for (int j = 0; j < 7; j++)
            sts32(sm + OFF_W + g * H_STRIDE + j * 128 + w * 16 + t * 4,
                  pack_bf16(round_bf16(sigmoid(round_bf16(acc[0][j][0]))) * round_bf16(acc[1][j][0]),
                            round_bf16(sigmoid(round_bf16(acc[0][j][1]))) * round_bf16(acc[1][j][1])));
        consumer_sync();
        float c[4][4] = {};
#pragma unroll 1
        for (int k = 0; k < FF_SLICE / 16; k++) {
            uint32_t b[4];
            ldsm4(b, sm + OFF_W + sw * H_STRIDE + (lane >> 3) * 16 + k * 32);
            mbar_wait(bar_full + 8 * slot, phase);
#pragma unroll
            for (int j = 0; j < 4; j++) {
                uint32_t a[4];
                ldsm4t(a, sm + slot * STAGE + w * 2048 + (sw + k_sel * 8) * 128 + (((j * 2 + v_sel) ^ sw) << 4));
                mma(c[j], a[0], a[1], a[2], a[3], b[0], b[1]);
            }
            __syncwarp();
            if (lane == 0) mbar_arrive(bar_empty + 8 * slot);
            if (++slot == NSLOT) { slot = 0; phase ^= 1; }
        }
#pragma unroll
        for (int j = 0; j < 4; j++) {
            uint32_t* dst = g_down + ((cta - N_ATT) * DM + w * 64 + j * 16 + g) * 8 + t * 2;
            put2(1, dst, c[j][0], c[j][1], tag);
            put2(1, dst + 64, c[j][2], c[j][3], tag);
        }
        if (tid == 0) g_epoch[cta] = epoch;
        return;
    }

    const int batch = cta >> 4, hkv = (cta >> 1) & 7, half = cta & 1;

    if (w < 4) {
        float acc[2][4] = {};
        const uint32_t b_addr = sm + OFF_W + lane * 64 + ((w ^ ((lane >> 1) & 3)) << 4);
#pragma unroll 1
        for (int kh = 0; kh < 4; kh++) {
            mbar_wait(bar_wq + (kh >> 1) * 8, 0);
#pragma unroll
            for (int k = 0; k < 4; k++) {
                uint32_t a[4], b[4];
                ldsm4(a, xn_addr + kh * 256 + k * 64);
                ldsm4t(b, b_addr + kh * 8192 + k * 2048);
                mma(acc[0], a[0], 0, a[1], 0, b[0], b[1]);
                mma(acc[1], a[2], 0, a[3], 0, b[2], b[3]);
            }
        }
        put_pair(g_q + g * 2048 + cta * 16 + w * 4 + t, pack_bf16(acc[0][0] + acc[1][0], acc[0][1] + acc[1][1]), epoch);
    }

    float o[8][4] = {};
    float m0 = -INFINITY, m1 = -INFINITY;
    const int head = cta >> 2;
    uint32_t* const opart_dst = g_opart + (((hkv * 4 + (t & 1) * 2) * 8 + batch) * 2 + half) * 128 + w * 16 + g;
    uint32_t* const stat_dst = g_stat + (((hkv * 4 + (t & 1) * 2) * 8 + batch) * 2 + half) * 2;
    uint32_t* const part_dst = g_part + ((head * 4 + t) * DM + (cta & 3) * 128 + w * 16 + g) * 2;
    const uint32_t* const down_src = g_down + out_col * 8 + out_batch;

    uint32_t live;
    asm volatile("mov.u32 %0, 0;" : "=r"(live));
#pragma unroll 1
    for (;; live = 1) {
        if (live) {
            sts32(sm + OFF_Q + (tid >> 6) * 272 + (tid & 63) * 4, get_pair((unsigned long long)~epoch << 32, g_q + batch * 2048 + hkv * 256 + tid, epoch));
            consumer_sync();
            uint32_t qf[8][2];
#pragma unroll
            for (int j = 0; j < 8; j++) {
                const uint32_t a = sm + OFF_Q + (g & 3) * 272 + j * 32 + t * 4;
                qf[j][0] = g < 4 ? lds32(a) : 0u;
                qf[j][1] = g < 4 ? lds32(a + 16) : 0u;
            }

            const uint32_t k_off = ((w & 3) * 16 + sw + v_sel * 8) * 128;
            const uint32_t v_off = ((w & 3) * 16 + sw + k_sel * 8) * 128;
            float l0 = 0.f, l1 = 0.f;
            auto reset_exchange = [&]() {
                const uint32_t none = tag ^ 2u;
                put1(1, opart_dst + (t >> 1) * 8, 0.f, none);
                put1(1, opart_dst + (t >> 1) * 8 + 8 * 2 * 128, 0.f, none);
                put2(tid < 2, stat_dst, 0.f, 0.f, none);
                put2(tid < 2, stat_dst + 8 * 4, 0.f, 0.f, none);
                put2(1, part_dst, 0.f, 0.f, none);
                put2(1, part_dst + 16, 0.f, 0.f, none);
            };
            int slot = w >> 2;
            uint32_t phase = 0;
#pragma unroll 1
            for (int it = 0;; it++) {
                uint32_t sa = 0, sb = 0, sa_prev, sb_prev, mx = 0xff80ff80u;
                int tiles = it == LAST ? 2 : 1;
                if (it == RESET_STEP) reset_exchange();
#pragma unroll 1
                do {
                    mbar_wait(bar_full + 8 * slot, phase);
                    float s[2][4] = {};
                    const uint32_t base = sm + slot * STAGE + k_off;
#pragma unroll
                    for (int j = 0; j < 8; j++) {
                        uint32_t a[4];
                        ldsm4(a, base + (j >> 2) * 8192 + ((((j & 3) * 2 + k_sel) ^ sw) << 4));
                        mma(s[j & 1], a[0], a[1], a[2], a[3], qf[j][0], qf[j][1]);
                    }
                    __syncwarp();
                    if (lane == 0) mbar_arrive(bar_empty + 8 * slot);
                    slot += 2;
                    if (slot >= NSLOT) { slot -= NSLOT; phase ^= 1; }
                    sa_prev = sa;
                    sb_prev = sb;
                    sa = pack_bf16(s[0][0] + s[1][0], s[0][1] + s[1][1]);
                    sb = pack_bf16(s[0][2] + s[1][2], s[0][3] + s[1][3]);
                    sa = pack_bf16(bf_lo(sa) * QK_SCALE, bf_hi(sa) * QK_SCALE);
                    sb = pack_bf16(bf_lo(sb) * QK_SCALE, bf_hi(sb) * QK_SCALE);
                    mx = max_bf16x2(mx, max_bf16x2(sa, sb));
                } while (--tiles);
                mx = max_bf16x2(mx, __shfl_xor_sync(~0u, mx, 4));
                mx = max_bf16x2(mx, __shfl_xor_sync(~0u, mx, 8));
                mx = max_bf16x2(mx, __shfl_xor_sync(~0u, mx, 16));
                float n0 = fmaxf(m0, bf_lo(mx)), n1 = fmaxf(m1, bf_hi(mx));
                const bool cta_wide = it == 0 || it == LAST;
                if (cta_wide) {
                    sts64_if(lane < 2, sm + OFF_STAT + w * 16 + t * 8, n0, n1);
                    consumer_sync();
#pragma unroll
                    for (int i = 0; i < 8; i++) {
                        const float2 v = lds64f(sm + OFF_STAT + i * 16 + (t & 1) * 8);
                        if (t < 2) { n0 = fmaxf(n0, v.x); n1 = fmaxf(n1, v.y); }
                    }
                }
                if (__any_sync(~0u, n0 != m0 || n1 != m1)) {
                    const float c0 = ex2((m0 - n0) * LOG2E), c1 = ex2((m1 - n1) * LOG2E);
                    l0 *= c0;
                    l1 *= c1;
#pragma unroll
                    for (int i = 0; i < 8; i++) { o[i][0] *= c0; o[i][1] *= c1; o[i][2] *= c0; o[i][3] *= c1; }
                    m0 = n0;
                    m1 = n1;
                }
                const float p0 = ex2((bf_lo(sa) - m0) * LOG2E), p1 = ex2((bf_hi(sa) - m1) * LOG2E);
                const float p2 = ex2((bf_lo(sb) - m0) * LOG2E), p3 = ex2((bf_hi(sb) - m1) * LOG2E);
                l0 += p0 + p2;
                l1 += p1 + p3;
                const uint32_t pb0 = transpose8x8(pack_bf16(p0, p1)), pb1 = transpose8x8(pack_bf16(p2, p3));
                if (it == LAST) {
                    const float e0 = ex2((bf_lo(sa_prev) - m0) * LOG2E), e1 = ex2((bf_hi(sa_prev) - m1) * LOG2E);
                    const float e2 = ex2((bf_lo(sb_prev) - m0) * LOG2E), e3 = ex2((bf_hi(sb_prev) - m1) * LOG2E);
                    sts64(sm + OFF_P + tid * 8, transpose8x8(pack_bf16(e0, e1)), transpose8x8(pack_bf16(e2, e3)));
                    sts64(sm + OFF_P + 2048 + tid * 8, pb0, pb1);
                    float r0 = l0 + (e0 + e2), r1 = l1 + (e1 + e3);
#pragma unroll
                    for (int off = 4; off < 32; off <<= 1) {
                        r0 += __shfl_xor_sync(~0u, r0, off);
                        r1 += __shfl_xor_sync(~0u, r1, off);
                    }
                    sts64_if(lane < 2, sm + OFF_STAT + 128 + w * 16 + t * 8, r0, r1);
                    break;
                }

                mbar_wait(bar_full + 8 * slot, phase);
                {
                    const uint32_t base = sm + slot * STAGE + v_off;
#pragma unroll
                    for (int i = 0; i < 8; i++) {
                        uint32_t a[4];
                        ldsm4t(a, base + (i >> 2) * 8192 + ((((i & 3) * 2 + v_sel) ^ sw) << 4));
                        mma(o[i], a[0], a[1], a[2], a[3], pb0, pb1);
                    }
                }
                __syncwarp();
                if (lane == 0) mbar_arrive(bar_empty + 8 * slot);
                slot += 2;
                if (slot >= NSLOT) { slot -= NSLOT; phase ^= 1; }
            }
        }

        {
            constexpr int RED = ((4 * LAST) % NSLOT) * STAGE;
            const uint32_t on = live && t < 2;
#pragma unroll
            for (int i = 0; i < 8; i++) {
                const uint32_t a = sm + RED + w * 2048 + (i * 16 + g) * 16 + t * 8;
                sts64_if(on, a, o[i][0], o[i][1]);
                sts64_if(on, a + 128, o[i][2], o[i][3]);
            }
            consumer_sync();
            if (w == 0) {
                float L0 = 0.f, L1 = 0.f;
#pragma unroll
                for (int i = 0; i < 8; i++) {
                    const float2 v = lds64f(sm + OFF_STAT + 128 + i * 16 + (t & 1) * 8);
                    L0 += v.x;
                    L1 += v.y;
                }
                put2(live && lane < 2, stat_dst, m0, L0, tag);
                put2(live && lane < 2, stat_dst + 8 * 4, m1, L1, tag);
            }
            float c[4][4] = {};
            uint2 pf[16];
#pragma unroll
            for (int i = 0; i < 8; i++) {
                const float2 v = lds64f(sm + RED + i * 2048 + (w * 16 + g + (t >> 1) * 8) * 16 + (t & 1) * 8);
                c[0][0] += v.x;
                c[0][1] += v.y;
                pf[i] = lds64(sm + OFF_P + i * 256 + lane * 8);
                pf[i + 8] = lds64(sm + OFF_P + 2048 + i * 256 + lane * 8);
            }
            c[0][2] = __shfl_xor_sync(~0u, c[0][0], 2);
            c[0][3] = __shfl_xor_sync(~0u, c[0][1], 2);
            const uint32_t a_off = sm + (w >> 2) * 8192 + (sw + k_sel * 8) * 128 + ((((w & 3) * 2 + v_sel) ^ sw) << 4);
#pragma unroll
            for (int i = 0; i < 16; i++) {
                const int item = KV_ITEMS - 4 + i / 4;
                if (i % 4 == 0 && live) mbar_wait(bar_full + 8 * (item % NSLOT), (item / NSLOT) & 1);
                uint32_t a[4];
                ldsm4t(a, a_off + (item % NSLOT) * STAGE + (i % 4) * 2048);
                mma(c[i % 4], a[0], a[1], a[2], a[3], pf[i].x, pf[i].y);
            }
#pragma unroll
            for (int j = 0; j < 4; j++)
                put1(on, opart_dst + (j & 1) * 8 * 2 * 128 + (j >> 1) * 8, (c[0][j] + c[1][j]) + (c[2][j] + c[3][j]), tag);
        }

        uint4 dp = make_uint4(tag, tag, tag, tag);
        get1(live && w == 0, dp.x, down_src);
        get1(live && w == 0, dp.y, down_src + DM * 8);
        get1(live && w == 0, dp.z, down_src + 2 * DM * 8);
        get1(live && w == 0, dp.w, down_src + 3 * DM * 8);

        {
            const uint4 ready = make_uint4(tag, tag, tag, tag);
            uint4 st = ready, ua = ready, ub = ready;
            const uint32_t* src = g_opart + (head * 8 + w) * 256 + lane * 4;
            uint32_t spins = 0, want_st = live, want_a = live, want_b = live, want_w = 1;
            float wa, wb;
            uint32_t a[8][4];
            const uint32_t a_off = sm + OFF_W + (w >> 2) * 16384 + (sw + k_sel * 8) * 128 + ((((w & 3) * 2 + v_sel) ^ sw) << 4);
            do {
                get4(want_st, st, g_stat + (head * 8 + w) * 4);
                get4(want_a, ua, src);
                get4(want_b, ub, src + 128);
                const float ma = __uint_as_float(st.x & ~3u), mb = __uint_as_float(st.z & ~3u);
                const float mm = fmaxf(ma, mb);
                wa = ex2((ma - mm) * LOG2E);
                wb = ex2((mb - mm) * LOG2E);
                const float inv = rcp(wa * __uint_as_float(st.y) + wb * __uint_as_float(st.w));
                wa *= inv;
                wb *= inv;
                asm volatile("" : "+f"(wa), "+f"(wb));
                if (want_w && __all_sync(~0u, !live || mbar_test(bar_wo, 0))) {
                    want_w = 0;
#pragma unroll
                    for (int k = 0; k < 8; k++) ldsm4t(a[k], a_off + k * 2048);
                }
                want_st = stale(st, tag);
                want_a = stale(ua, tag);
                want_b = stale(ub, tag);
                if (++spins > SPIN_LIMIT) __trap();
            } while (__any_sync(~0u, want_st | want_a | want_b | want_w));
            sts64(sm + OFF_O + w * O_STRIDE + lane * 8,
                  pack_bf16(wa * __uint_as_float(ua.x) + wb * __uint_as_float(ub.x), wa * __uint_as_float(ua.y) + wb * __uint_as_float(ub.y)),
                  pack_bf16(wa * __uint_as_float(ua.z) + wb * __uint_as_float(ub.z), wa * __uint_as_float(ua.w) + wb * __uint_as_float(ub.w)));
            consumer_sync();
            float c[4][4] = {};
#pragma unroll
            for (int k = 0; k < 4; k++) {
                uint32_t b[4];
                ldsm4(b, sm + OFF_O + sw * O_STRIDE + (lane >> 3) * 16 + k * 64);
                mma(c[(k & 1) * 2], a[2 * k][0], a[2 * k][1], a[2 * k][2], a[2 * k][3], b[0], b[1]);
                mma(c[(k & 1) * 2 + 1], a[2 * k + 1][0], a[2 * k + 1][1], a[2 * k + 1][2], a[2 * k + 1][3], b[2], b[3]);
            }
            put2(live, part_dst, (c[0][0] + c[1][0]) + (c[2][0] + c[3][0]), (c[0][1] + c[1][1]) + (c[2][1] + c[3][1]), tag);
            put2(live, part_dst + 16, (c[0][2] + c[1][2]) + (c[2][2] + c[3][2]), (c[0][3] + c[1][3]) + (c[2][3] + c[3][3]), tag);
        }

        float gate;
        {
            uint32_t spins = 0;
            while (stale(dp, tag)) {
                get1(1, dp.x, down_src);
                get1(1, dp.y, down_src + DM * 8);
                get1(1, dp.z, down_src + 2 * DM * 8);
                get1(1, dp.w, down_src + 3 * DM * 8);
                if (++spins > SPIN_LIMIT) __trap();
            }
            const float d = round_bf16((__uint_as_float(dp.x) + __uint_as_float(dp.y)) + (__uint_as_float(dp.z) + __uint_as_float(dp.w)));
            gate = round_bf16(d * sigmoid(d));
        }

        {
            const uint32_t* src = g_part + (((w * 4 + (lane >> 3)) * 4 + (cta & 3)) * DM + (cta >> 2) * 16) * 2 + (lane & 7) * 4;
            uint4 u = make_uint4(tag, tag, tag, tag);
            uint32_t pending = live, spins = 0;
            do {
                get4(pending, u, src);
                pending = stale(u, tag);
                if (++spins > SPIN_LIMIT) __trap();
            } while (pending);
            __syncwarp();
            const bool up = lane & 16, b3 = lane & 8;
            const float a0 = __uint_as_float(up ? u.z : u.x) + __shfl_xor_sync(~0u, __uint_as_float(up ? u.x : u.z), 16);
            const float a1 = __uint_as_float(up ? u.w : u.y) + __shfl_xor_sync(~0u, __uint_as_float(up ? u.y : u.w), 16);
            const float r = (b3 ? a1 : a0) + __shfl_xor_sync(~0u, b3 ? a0 : a1, 8);
            sts32(sm + OFF_P + w * 128 + ((lane & 7) * 4 + (lane >> 4) * 2 + ((lane >> 3) & 1)) * 4, __float_as_uint(r));
            consumer_sync();
            if (w == 0) {
                float v[8];
#pragma unroll
                for (int i = 0; i < 8; i++) v[i] = __uint_as_float(lds32(sm + OFF_P + i * 128 + lane * 4));
                const float sv = round_bf16(((v[0] + v[1]) + (v[2] + v[3])) + ((v[4] + v[5]) + (v[6] + v[7])));
                const uint32_t res = pack_bf16(x_res + round_bf16(sv * gate), 0.f);
                asm volatile("{\n.reg .pred p;\n.reg .b16 lo, hi;\nsetp.ne.u32 p, %0, 0;\nmov.b32 {lo, hi}, %2;\n@p st.global.b16 [%1], lo;\n}"
                             ::"r"(live), "l"(out + out_batch * DM + out_col), "r"(res) : "memory");
                if (live && lane == 0) g_epoch[cta] = epoch;
            }
        }
        if (live) break;
    }
}

using EncodeFn = CUresult (*)(CUtensorMap*, CUtensorMapDataType, cuuint32_t, void*, const cuuint64_t*, const cuuint64_t*,
                              const cuuint32_t*, const cuuint32_t*, CUtensorMapInterleave, CUtensorMapSwizzle,
                              CUtensorMapL2promotion, CUtensorMapFloatOOBfill);

void encode(EncodeFn fn, CUtensorMap* m, void* p, cuuint64_t rows, cuuint64_t cols, cuuint32_t box_rows, cuuint32_t box_cols,
            cuuint32_t width = 64) {
    const cuuint64_t dims[3] = {width, rows, cols / width}, strides[2] = {cols * 2, width * 2};
    const cuuint32_t box[3] = {width, box_rows, box_cols / width}, elem[3] = {1, 1, 1};
    fn(m, CU_TENSOR_MAP_DATA_TYPE_BFLOAT16, 3, p, dims, strides, box, elem, CU_TENSOR_MAP_INTERLEAVE_NONE,
       width == 64 ? CU_TENSOR_MAP_SWIZZLE_128B : CU_TENSOR_MAP_SWIZZLE_64B, CU_TENSOR_MAP_L2_PROMOTION_L2_256B,
       CU_TENSOR_MAP_FLOAT_OOB_FILL_NONE);
}

}

extern "C" void kernel_launch(void* const* d_in, const int* in_sizes, int n_in, void* d_out, int out_size) {
    (void)in_sizes; (void)n_in; (void)out_size;
    static EncodeFn fn = nullptr;
    if (!fn) {
        cudaDriverEntryPointQueryResult status;
        cudaGetDriverEntryPoint("cuTensorMapEncodeTiled", (void**)&fn, cudaEnableDefault, &status);
        cudaFuncSetAttribute(decode_kernel, cudaFuncAttributeMaxDynamicSharedMemorySize, SMEM_BYTES);
    }
    Maps maps;
    encode(fn, &maps.m[MAP_K], d_in[1], 8 * 8 * 4096, 128, 64, 128);
    encode(fn, &maps.m[MAP_V], d_in[2], 8 * 8 * 4096, 128, 64, 128);
    encode(fn, &maps.m[MAP_WQ], d_in[3], DM, 4096, 256, 32, 32);
    encode(fn, &maps.m[MAP_WO], d_in[4], 4096, DM, 128, 128);
    encode(fn, &maps.m[MAP_WG], d_in[6], DM, FF, 16, FF_SLICE);
    encode(fn, &maps.m[MAP_WU], d_in[7], DM, FF, 16, FF_SLICE);
    encode(fn, &maps.m[MAP_WD], d_in[8], FF, DM, 16, DM);
    decode_kernel<<<GRID, N_THREADS, SMEM_BYTES>>>(maps, (const __nv_bfloat16*)d_in[0], (__nv_bfloat16*)d_out);
}
```

```cpp
#include <cuda.h>
#include <cuda_bf16.h>
#include <cuda_runtime.h>
#include <stdint.h>

namespace {

constexpr int DM = 512, FF = 1792;
constexpr int N_ATT = 128, N_FFN = 4, GRID = N_ATT + N_FFN;
constexpr int N_THREADS = 320;
constexpr int STAGE = 16384, NSLOT = 10;
constexpr int KV_ITEMS = 64;
constexpr int LAST = 14;
constexpr int FF_SLICE = FF / N_FFN;
constexpr int GU_ITEMS = 2 * DM / 16;
constexpr int FFN_ITEMS = GU_ITEMS + FF_SLICE / 16;

constexpr int WIN_HEAD = 3, HEAD_ITEMS = 6, WIN_BODY = 4, WIN_FFN = 10;
constexpr int LAG_1 = 48, LAG_2 = 128, LEAD_1 = 160;
constexpr int TAIL_ITEMS = 8, WIN_TAIL = 10, WIN_TAIL_LEAD = 5, TAIL_LEAD = 192;
constexpr int GATE_LEFT = 640;
constexpr int RESET_STEP = 10;

constexpr int OFF_W = NSLOT * STAGE;
constexpr int H_STRIDE = 912;
constexpr int OFF_XN = OFF_W + 32768;
constexpr int XN_STRIDE = 1040;
constexpr int OFF_Q = OFF_XN + 8 * XN_STRIDE;
constexpr int OFF_O = OFF_Q + 4 * 272;
constexpr int O_STRIDE = 272;
constexpr int OFF_STAT = OFF_O + 8 * O_STRIDE;
constexpr int OFF_P = OFF_STAT + 256;
constexpr int OFF_BAR = OFF_P + 4096;
constexpr int OFF_CTL = OFF_BAR + 240;
constexpr int SMEM_BYTES = OFF_BAR + 256 + 1024;

constexpr float LOG2E = 1.4426950408889634f;
constexpr float QK_SCALE = 0.08838834764831845f;
constexpr uint32_t SPIN_LIMIT = 1u << 24;

enum { MAP_K, MAP_V, MAP_WQ, MAP_WG, MAP_WU, MAP_WD, MAP_WO, N_MAPS };
struct Maps { CUtensorMap m[N_MAPS]; };

__device__ uint32_t g_epoch[GRID];
__device__ uint32_t g_progress;
__device__ unsigned long long g_q[8 * 2048];
__device__ __align__(128) uint32_t g_opart[32 * 8 * 2 * 128];
__device__ __align__(128) uint32_t g_stat[32 * 8 * 4];
__device__ __align__(128) uint32_t g_part[32 * DM * 8];
__device__ __align__(128) uint32_t g_down[N_FFN * DM * 8];

__device__ __forceinline__ void mbar_init(uint32_t bar, uint32_t count) {
    asm volatile("mbarrier.init.shared::cta.b64 [%0], %1;" ::"r"(bar), "r"(count) : "memory");
}
__device__ __forceinline__ void mbar_expect_tx(uint32_t bar, uint32_t bytes) {
    asm volatile("mbarrier.arrive.expect_tx.shared::cta.b64 _, [%0], %1;" ::"r"(bar), "r"(bytes) : "memory");
}
__device__ __forceinline__ void mbar_arrive(uint32_t bar) {
    asm volatile("mbarrier.arrive.shared::cta.b64 _, [%0];" ::"r"(bar) : "memory");
}
__device__ __forceinline__ uint32_t mbar_test(uint32_t bar, uint32_t parity) {
    uint32_t ok;
    asm volatile("{\n.reg .pred p;\nmbarrier.test_wait.parity.shared::cta.b64 p, [%1], %2;\nselp.u32 %0, 1, 0, p;\n}"
                 : "=r"(ok) : "r"(bar), "r"(parity) : "memory");
    return ok;
}
__device__ __forceinline__ void mbar_wait(uint32_t bar, uint32_t parity) {
    uint32_t ok, spins = 0;
    do {
        asm volatile("{\n.reg .pred p;\nmbarrier.try_wait.parity.shared::cta.b64 p, [%1], %2;\nselp.u32 %0, 1, 0, p;\n}"
                     : "=r"(ok) : "r"(bar), "r"(parity) : "memory");
        if (++spins > SPIN_LIMIT) __trap();
    } while (!ok);
}
__device__ __forceinline__ void tma_load(uint32_t dst, const CUtensorMap* m, int row, int block, uint32_t bar) {
    asm volatile("{\n.reg .b64 policy;\ncreatepolicy.fractional.L2::evict_first.b64 policy, 1.0;\n"
                 "cp.async.bulk.tensor.3d.shared::cluster.global.mbarrier::complete_tx::bytes.L2::cache_hint [%0], [%1, {%3, %4, %5}], [%2], policy;\n}"
                 ::"r"(dst), "l"(m), "r"(bar), "r"(0), "r"(row), "r"(block) : "memory");
}
__device__ __forceinline__ void consumer_sync() { asm volatile("bar.sync 1, 256;" ::: "memory"); }
__device__ __forceinline__ void ldsm4(uint32_t (&r)[4], uint32_t addr) {
    asm volatile("ldmatrix.sync.aligned.m8n8.x4.shared.b16 {%0,%1,%2,%3}, [%4];"
                 : "=r"(r[0]), "=r"(r[1]), "=r"(r[2]), "=r"(r[3]) : "r"(addr) : "memory");
}
__device__ __forceinline__ void ldsm4t(uint32_t (&r)[4], uint32_t addr) {
    asm volatile("ldmatrix.sync.aligned.m8n8.x4.trans.shared.b16 {%0,%1,%2,%3}, [%4];"
                 : "=r"(r[0]), "=r"(r[1]), "=r"(r[2]), "=r"(r[3]) : "r"(addr) : "memory");
}
__device__ __forceinline__ void mma(float (&c)[4], uint32_t a0, uint32_t a1, uint32_t a2, uint32_t a3, uint32_t b0, uint32_t b1) {
    asm volatile("mma.sync.aligned.m16n8k16.row.col.f32.bf16.bf16.f32 {%0,%1,%2,%3}, {%4,%5,%6,%7}, {%8,%9}, {%0,%1,%2,%3};"
                 : "+f"(c[0]), "+f"(c[1]), "+f"(c[2]), "+f"(c[3])
                 : "r"(a0), "r"(a1), "r"(a2), "r"(a3), "r"(b0), "r"(b1));
}
__device__ __forceinline__ uint32_t transpose8x8(uint32_t a) {
    uint32_t d;
    asm volatile("movmatrix.sync.aligned.m8n8.trans.b16 %0, %1;" : "=r"(d) : "r"(a));
    return d;
}
__device__ __forceinline__ uint32_t pack_bf16(float lo, float hi) {
    uint32_t d;
    asm("cvt.rn.bf16x2.f32 %0, %1, %2;" : "=r"(d) : "f"(hi), "f"(lo));
    return d;
}
__device__ __forceinline__ float bf_lo(uint32_t v) { return __uint_as_float(v << 16); }
__device__ __forceinline__ float bf_hi(uint32_t v) { return __uint_as_float(v & 0xffff0000u); }
__device__ __forceinline__ float round_bf16(float v) { return bf_lo(pack_bf16(v, 0.f)); }
__device__ __forceinline__ uint32_t max_bf16x2(uint32_t a, uint32_t b) {
    uint32_t d;
    asm("max.bf16x2 %0, %1, %2;" : "=r"(d) : "r"(a), "r"(b));
    return d;
}
__device__ __forceinline__ float ex2(float x) {
    float y;
    asm("ex2.approx.ftz.f32 %0, %1;" : "=f"(y) : "f"(x));
    return y;
}
__device__ __forceinline__ float rcp(float x) {
    float y;
    asm("rcp.approx.ftz.f32 %0, %1;" : "=f"(y) : "f"(x));
    return y;
}
__device__ __forceinline__ float sqrt_approx(float x) {
    float y;
    asm("sqrt.approx.ftz.f32 %0, %1;" : "=f"(y) : "f"(x));
    return y;
}
__device__ __forceinline__ float sigmoid(float x) { return rcp(1.f + ex2(-x * LOG2E)); }
__device__ __forceinline__ void sts32(uint32_t addr, uint32_t v) { asm volatile("st.shared.b32 [%0], %1;" ::"r"(addr), "r"(v) : "memory"); }
__device__ __forceinline__ void sts64(uint32_t addr, uint32_t a, uint32_t b) { asm volatile("st.shared.v2.b32 [%0], {%1,%2};" ::"r"(addr), "r"(a), "r"(b) : "memory"); }
__device__ __forceinline__ uint32_t lds32(uint32_t addr) {
    uint32_t v;
    asm volatile("ld.shared.b32 %0, [%1];" : "=r"(v) : "r"(addr) : "memory");
    return v;
}
__device__ __forceinline__ uint2 lds64(uint32_t addr) {
    uint2 v;
    asm volatile("ld.shared.v2.b32 {%0,%1}, [%2];" : "=r"(v.x), "=r"(v.y) : "r"(addr) : "memory");
    return v;
}
__device__ __forceinline__ float2 lds64f(uint32_t addr) {
    float2 v;
    asm volatile("ld.shared.v2.f32 {%0,%1}, [%2];" : "=f"(v.x), "=f"(v.y) : "r"(addr) : "memory");
    return v;
}

__device__ __forceinline__ void sts64_if(uint32_t on, uint32_t addr, float a, float b) {
    asm volatile("{\n.reg .pred p;\nsetp.ne.u32 p, %0, 0;\n@p st.shared.v2.f32 [%1], {%2,%3};\n}" ::"r"(on), "r"(addr), "f"(a), "f"(b) : "memory");
}

__device__ __forceinline__ void put_pair(unsigned long long* p, uint32_t data, uint32_t epoch) {
    asm volatile("st.relaxed.gpu.global.b64 [%0], %1;" ::"l"(p), "l"(((unsigned long long)epoch << 32) | data) : "memory");
}
__device__ __forceinline__ uint32_t get_pair(const unsigned long long* p, uint32_t epoch) {
    unsigned long long v;
    uint32_t spins = 0;
    do {
        asm volatile("ld.relaxed.gpu.global.b64 %0, [%1];" : "=l"(v) : "l"(p) : "memory");
        if (++spins > SPIN_LIMIT) __trap();
    } while ((uint32_t)(v >> 32) != epoch);
    return (uint32_t)v;
}
__device__ __forceinline__ uint32_t tagged(float v, uint32_t tag) { return (__float_as_uint(v) & ~3u) | tag; }
__device__ __forceinline__ void put1(uint32_t on, uint32_t* p, float a, uint32_t tag) {
    asm volatile("{\n.reg .pred p;\nsetp.ne.u32 p, %0, 0;\n@p st.relaxed.gpu.global.b32 [%1], %2;\n}" ::"r"(on), "l"(p), "r"(tagged(a, tag)) : "memory");
}
__device__ __forceinline__ void put2(uint32_t on, uint32_t* p, float a, float b, uint32_t tag) {
    asm volatile("{\n.reg .pred p;\nsetp.ne.u32 p, %0, 0;\n@p st.relaxed.gpu.global.v2.b32 [%1], {%2,%3};\n}"
                 ::"r"(on), "l"(p), "r"(tagged(a, tag)), "r"(tagged(b, tag)) : "memory");
}
__device__ __forceinline__ void get1(uint32_t on, uint32_t& v, const uint32_t* p) {
    asm volatile("{\n.reg .pred p;\nsetp.ne.u32 p, %2, 0;\n@p ld.relaxed.gpu.global.b32 %0, [%1];\n}" : "+r"(v) : "l"(p), "r"(on) : "memory");
}
__device__ __forceinline__ void get4(uint32_t on, uint4& v, const uint32_t* p) {
    asm volatile("{\n.reg .pred p;\nsetp.ne.u32 p, %5, 0;\n@p ld.relaxed.gpu.global.v4.b32 {%0,%1,%2,%3}, [%4];\n}"
                 : "+r"(v.x), "+r"(v.y), "+r"(v.z), "+r"(v.w) : "l"(p), "r"(on) : "memory");
}
__device__ __forceinline__ uint32_t stale(const uint4& v, uint32_t tag) {
    return ((v.x ^ tag) | (v.y ^ tag) | (v.z ^ tag) | (v.w ^ tag)) & 3u;
}

__device__ __forceinline__ void layernorm_row(const uint4& u0, const uint4& u1, int lane, uint32_t xn_row) {
    const uint32_t u[8] = {u0.x, u0.y, u0.z, u0.w, u1.x, u1.y, u1.z, u1.w};
    float v[16], sum = 0.f;
#pragma unroll
    for (int i = 0; i < 8; i++) { v[2 * i] = bf_lo(u[i]); v[2 * i + 1] = bf_hi(u[i]); sum += v[2 * i] + v[2 * i + 1]; }
#pragma unroll
    for (int o = 16; o > 0; o >>= 1) sum += __shfl_xor_sync(~0u, sum, o);
    const float mean = sum * (1.f / DM);
    float sq = 0.f;
#pragma unroll
    for (int i = 0; i < 16; i++) sq += (v[i] - mean) * (v[i] - mean);
#pragma unroll
    for (int o = 16; o > 0; o >>= 1) sq += __shfl_xor_sync(~0u, sq, o);
    const float mean_b = round_bf16(mean);
    const float inv = rcp(round_bf16(sqrt_approx(round_bf16(round_bf16(sq * (1.f / DM)) + 1e-5f))));
    uint32_t r[8];
#pragma unroll
    for (int i = 0; i < 8; i++) r[i] = pack_bf16(round_bf16(v[2 * i] - mean_b) * inv, round_bf16(v[2 * i + 1] - mean_b) * inv);
    asm volatile("st.shared.v4.b32 [%0], {%1,%2,%3,%4};" ::"r"(xn_row + lane * 16), "r"(r[0]), "r"(r[1]), "r"(r[2]), "r"(r[3]) : "memory");
    asm volatile("st.shared.v4.b32 [%0], {%1,%2,%3,%4};" ::"r"(xn_row + 512 + lane * 16), "r"(r[4]), "r"(r[5]), "r"(r[6]), "r"(r[7]) : "memory");
}

__global__ void __launch_bounds__(N_THREADS, 1)
decode_kernel(const __grid_constant__ Maps maps, const __nv_bfloat16* __restrict__ x, __nv_bfloat16* __restrict__ out) {
    extern __shared__ __align__(1024) unsigned char smem_raw[];
    const uint32_t sm = ((uint32_t)__cvta_generic_to_shared(smem_raw) + 1023u) & ~1023u;
    const uint32_t bar_wq = sm + OFF_BAR, bar_full = bar_wq + 16, bar_wo = bar_full + 8 * NSLOT, bar_empty = bar_wo + 8;
    const int tid = threadIdx.x, w = tid >> 5, lane = tid & 31;
    const int cta = blockIdx.x;
    const bool att = cta < N_ATT;

    if (__builtin_expect(tid == 256 && att, 1)) {
#pragma unroll
        for (int i = 0; i < 3; i++) mbar_init(bar_wq + 8 * i, 1);
        asm volatile("fence.proxy.async.shared::cta;" ::: "memory");
#pragma unroll
        for (int i = 0; i < 2; i++) {
            mbar_expect_tx(bar_wq + 8 * i, STAGE);
            tma_load(sm + OFF_W + i * STAGE, &maps.m[MAP_WQ], i * 256, cta, bar_wq + 8 * i);
        }
        mbar_expect_tx(bar_full, STAGE);
        tma_load(sm, &maps.m[MAP_K], cta * 2048, 0, bar_full);
    }

    if (w == 8) {
        __syncwarp();
        asm volatile("bar.arrive 0, 320;" ::: "memory");
        asm volatile("bar.sync 2, 64;" ::: "memory");
        if (lane != 0) return;
        const int n_ring = att ? KV_ITEMS : FFN_ITEMS;
        int landed = att ? -2 : 0, slot = att ? 1 : 0, lslot = 0;
        uint32_t phase = 1, lphase = 0;
        auto count_landed = [&]() {
            if (landed >= 0) {
                if (++lslot == NSLOT) { lslot = 0; lphase ^= 1; }
                if (att) asm volatile("red.relaxed.gpu.global.add.u32 [%0], 1;" ::"l"(&g_progress) : "memory");
            }
            landed++;
        };
#pragma unroll 1
        for (int n = slot; n < n_ring; n++) {
            int win = WIN_FFN;
            if (att) {
                const int lead = N_ATT * landed - (int)lds32(sm + OFF_CTL);
                win = WIN_BODY + (lead < -LAG_1) + (lead < -LAG_2) - (lead > LEAD_1);
                if (n < HEAD_ITEMS) win = WIN_HEAD;
                if (n >= KV_ITEMS - TAIL_ITEMS) win = lead > TAIL_LEAD ? WIN_TAIL_LEAD : WIN_TAIL;
            }
#pragma unroll 1
            while (landed <= n - win || (landed < n && mbar_test(bar_full + 8 * (landed < 0 ? landed : lslot), lphase))) {
                mbar_wait(bar_full + 8 * (landed < 0 ? landed : lslot), lphase);
                count_landed();
            }
            mbar_wait(bar_empty + 8 * slot, phase);
            const uint32_t bar = bar_full + 8 * slot;
            mbar_expect_tx(bar, att || n >= GU_ITEMS ? STAGE : 32 * FF_SLICE);
            int map = MAP_K + ((n >> 1) & 1), row = cta * 2048 + (n >> 2) * 128 + (n & 1) * 64, block = 0;
            if (n >= 4 * LAST) {
                map = MAP_K + ((n >> 2) & 1);
                row = cta * 2048 + LAST * 128 + (n & 3) * 64;
            }
            if (!att) {
                const bool gu = n < GU_ITEMS;
                map = gu ? MAP_WG + (n & 1) : MAP_WD;
                row = gu ? (n >> 1) * 16 : (cta - N_ATT) * FF_SLICE + (n - GU_ITEMS) * 16;
                block = gu ? (cta - N_ATT) * (FF_SLICE / 64) : 0;
            }
            tma_load(sm + slot * STAGE, &maps.m[map], row, block, bar);
            if (++slot == NSLOT) { slot = 0; phase ^= 1; }
        }
        if (att) {
            uint32_t spins = 0;
            bool gated = true;
#pragma unroll 1
            while (gated || landed < KV_ITEMS) {
                if (landed < KV_ITEMS && mbar_test(bar_full + 8 * lslot, lphase)) count_landed();
                if (gated && (int)lds32(sm + OFF_CTL) >= N_ATT * KV_ITEMS - GATE_LEFT) {
                    gated = false;
                    mbar_expect_tx(bar_wo, 32768);
                    tma_load(sm + OFF_W, &maps.m[MAP_WO], (cta >> 2) * 128, (cta & 3) * 2, bar_wo);
                    sts32(sm + OFF_CTL + 4, 1);
                }
                if (++spins > SPIN_LIMIT) __trap();
            }
        }
        return;
    }
    if (w == 9) {
        if (lane == 0) {
#pragma unroll
            for (int i = 0; i < 2 * NSLOT + 3; i++)
                if (i >= 3 || !att) mbar_init(bar_wq + 8 * i, i < NSLOT + 3 ? 1 : att ? 4 : 8);
            sts64(sm + OFF_CTL, 0, 0);
            asm volatile("fence.proxy.async.shared::cta;" ::: "memory");
        }
        __syncwarp();
        asm volatile("bar.arrive 2, 64;" ::: "memory");
        asm volatile("bar.arrive 0, 320;" ::: "memory");
        if (lane == 0 && att) {
            uint32_t base, spins = 0;
            asm volatile("ld.relaxed.gpu.global.b32 %0, [%1];" : "=r"(base) : "l"(g_epoch + cta) : "memory");
            base *= N_ATT * KV_ITEMS;
            while (!lds32(sm + OFF_CTL + 4) && ++spins < SPIN_LIMIT) {
                uint32_t v;
                asm volatile("ld.relaxed.gpu.global.b32 %0, [%1];" : "=r"(v) : "l"(&g_progress) : "memory");
                sts32(sm + OFF_CTL, v - base);
            }
        }
        return;
    }

    const uint4* xr = reinterpret_cast<const uint4*>(x + w * DM);
    const uint4 xa = __ldg(xr + lane), xb = __ldg(xr + 32 + lane);
    uint32_t epoch;
    asm volatile("ld.relaxed.gpu.global.b32 %0, [%1];" : "=r"(epoch) : "l"(g_epoch + cta) : "memory");
    const int g = lane >> 2, t = lane & 3;
    const int out_batch = (cta & 3) * 2 + (lane & 1), out_col = (cta >> 2) * 16 + (lane >> 1);
    float x_res = 0.f;
    if (att && w == 0) x_res = __bfloat162float(__ldg(x + out_batch * DM + out_col));
    layernorm_row(xa, xb, lane, sm + OFF_XN + w * XN_STRIDE);
    epoch += 1;
    const uint32_t tag = epoch & 3u;
    asm volatile("bar.sync 0, 320;" ::: "memory");
    const uint32_t xn_addr = sm + OFF_XN + (lane & 7) * XN_STRIDE + (lane >> 3) * 16;
    const int sw = lane & 7;
    const int k_sel = lane >> 4, v_sel = (lane >> 3) & 1;

    if (!att) {
        int slot = 0;
        uint32_t phase = 0;
        float acc[2][7][4] = {};
#pragma unroll 1
        for (int k = 0; k < DM / 16; k++) {
            uint32_t a[4];
            ldsm4(a, xn_addr + k * 32);
#pragma unroll
            for (int u = 0; u < 2; u++) {
                mbar_wait(bar_full + 8 * slot, phase);
#pragma unroll
                for (int j = 0; j < 7; j += 2) {
                    uint32_t b[4];
                    ldsm4t(b, sm + slot * STAGE + j * 2048 + lane * 128 + ((w ^ sw) << 4));
                    mma(acc[u][j], a[0], 0, a[1], 0, b[0], b[1]);
                    if (j < 6) mma(acc[u][j + 1], a[0], 0, a[1], 0, b[2], b[3]);
                }
                __syncwarp();
                if (lane == 0) mbar_arrive(bar_empty + 8 * slot);
                if (++slot == NSLOT) { slot = 0; phase ^= 1; }
            }
        }
#pragma unroll
        for (int j = 0; j < 7; j++)
            sts32(sm + OFF_W + g * H_STRIDE + j * 128 + w * 16 + t * 4,
                  pack_bf16(round_bf16(sigmoid(round_bf16(acc[0][j][0]))) * round_bf16(acc[1][j][0]),
                            round_bf16(sigmoid(round_bf16(acc[0][j][1]))) * round_bf16(acc[1][j][1])));
        consumer_sync();
        float c[4][4] = {};
#pragma unroll 1
        for (int k = 0; k < FF_SLICE / 16; k++) {
            uint32_t b[4];
            ldsm4(b, sm + OFF_W + sw * H_STRIDE + (lane >> 3) * 16 + k * 32);
            mbar_wait(bar_full + 8 * slot, phase);
#pragma unroll
            for (int j = 0; j < 4; j++) {
                uint32_t a[4];
                ldsm4t(a, sm + slot * STAGE + w * 2048 + (sw + k_sel * 8) * 128 + (((j * 2 + v_sel) ^ sw) << 4));
                mma(c[j], a[0], a[1], a[2], a[3], b[0], b[1]);
            }
            __syncwarp();
            if (lane == 0) mbar_arrive(bar_empty + 8 * slot);
            if (++slot == NSLOT) { slot = 0; phase ^= 1; }
        }
#pragma unroll
        for (int j = 0; j < 4; j++) {
            uint32_t* dst = g_down + ((cta - N_ATT) * DM + w * 64 + j * 16 + g) * 8 + t * 2;
            put2(1, dst, c[j][0], c[j][1], tag);
            put2(1, dst + 64, c[j][2], c[j][3], tag);
        }
        if (tid == 0) g_epoch[cta] = epoch;
        return;
    }

    const int batch = cta >> 4, hkv = (cta >> 1) & 7, half = cta & 1;

    if (w < 4) {
        float acc[2][4] = {};
        const uint32_t b_addr = sm + OFF_W + lane * 64 + ((w ^ ((lane >> 1) & 3)) << 4);
#pragma unroll 1
        for (int kh = 0; kh < 4; kh++) {
            mbar_wait(bar_wq + (kh >> 1) * 8, 0);
#pragma unroll
            for (int k = 0; k < 4; k++) {
                uint32_t a[4], b[4];
                ldsm4(a, xn_addr + kh * 256 + k * 64);
                ldsm4t(b, b_addr + kh * 8192 + k * 2048);
                mma(acc[0], a[0], 0, a[1], 0, b[0], b[1]);
                mma(acc[1], a[2], 0, a[3], 0, b[2], b[3]);
            }
        }
        put_pair(g_q + g * 2048 + cta * 16 + w * 4 + t, pack_bf16(acc[0][0] + acc[1][0], acc[0][1] + acc[1][1]), epoch);
    }

    float o[8][4] = {};
    float m0 = -INFINITY, m1 = -INFINITY;
    const int head = cta >> 2;
    uint32_t* const opart_dst = g_opart + (((hkv * 4 + (t & 1) * 2) * 8 + batch) * 2 + half) * 128 + w * 16 + g;
    uint32_t* const stat_dst = g_stat + (((hkv * 4 + (t & 1) * 2) * 8 + batch) * 2 + half) * 2;
    uint32_t* const part_dst = g_part + ((head * 4 + t) * DM + (cta & 3) * 128 + w * 16 + g) * 2;
    const uint32_t* const down_src = g_down + out_col * 8 + out_batch;

    uint32_t live;
    asm volatile("mov.u32 %0, 0;" : "=r"(live));
#pragma unroll 1
    for (;; live = 1) {
        if (live) {
            sts32(sm + OFF_Q + (tid >> 6) * 272 + (tid & 63) * 4, get_pair(g_q + batch * 2048 + hkv * 256 + tid, epoch));
            consumer_sync();
            uint32_t qf[8][2];
#pragma unroll
            for (int j = 0; j < 8; j++) {
                const uint32_t a = sm + OFF_Q + (g & 3) * 272 + j * 32 + t * 4;
                qf[j][0] = g < 4 ? lds32(a) : 0u;
                qf[j][1] = g < 4 ? lds32(a + 16) : 0u;
            }

            const uint32_t k_off = ((w & 3) * 16 + sw + v_sel * 8) * 128;
            const uint32_t v_off = ((w & 3) * 16 + sw + k_sel * 8) * 128;
            float l0 = 0.f, l1 = 0.f;
            auto reset_exchange = [&]() {
                const uint32_t none = tag ^ 2u;
                put1(1, opart_dst + (t >> 1) * 8, 0.f, none);
                put1(1, opart_dst + (t >> 1) * 8 + 8 * 2 * 128, 0.f, none);
                put2(tid < 2, stat_dst, 0.f, 0.f, none);
                put2(tid < 2, stat_dst + 8 * 4, 0.f, 0.f, none);
                put2(1, part_dst, 0.f, 0.f, none);
                put2(1, part_dst + 16, 0.f, 0.f, none);
            };
            int slot = w >> 2;
            uint32_t phase = 0;
#pragma unroll 1
            for (int it = 0;; it++) {
                uint32_t sa = 0, sb = 0, sa_prev, sb_prev, mx = 0xff80ff80u;
                int tiles = it == LAST ? 2 : 1;
                if (it == RESET_STEP) reset_exchange();
#pragma unroll 1
                do {
                    mbar_wait(bar_full + 8 * slot, phase);
                    float s[2][4] = {};
                    const uint32_t base = sm + slot * STAGE + k_off;
#pragma unroll
                    for (int j = 0; j < 8; j++) {
                        uint32_t a[4];
                        ldsm4(a, base + (j >> 2) * 8192 + ((((j & 3) * 2 + k_sel) ^ sw) << 4));
                        mma(s[j & 1], a[0], a[1], a[2], a[3], qf[j][0], qf[j][1]);
                    }
                    __syncwarp();
                    if (lane == 0) mbar_arrive(bar_empty + 8 * slot);
                    slot += 2;
                    if (slot >= NSLOT) { slot -= NSLOT; phase ^= 1; }
                    sa_prev = sa;
                    sb_prev = sb;
                    sa = pack_bf16(s[0][0] + s[1][0], s[0][1] + s[1][1]);
                    sb = pack_bf16(s[0][2] + s[1][2], s[0][3] + s[1][3]);
                    sa = pack_bf16(bf_lo(sa) * QK_SCALE, bf_hi(sa) * QK_SCALE);
                    sb = pack_bf16(bf_lo(sb) * QK_SCALE, bf_hi(sb) * QK_SCALE);
                    mx = max_bf16x2(mx, max_bf16x2(sa, sb));
                } while (--tiles);
                mx = max_bf16x2(mx, __shfl_xor_sync(~0u, mx, 4));
                mx = max_bf16x2(mx, __shfl_xor_sync(~0u, mx, 8));
                mx = max_bf16x2(mx, __shfl_xor_sync(~0u, mx, 16));
                float n0 = fmaxf(m0, bf_lo(mx)), n1 = fmaxf(m1, bf_hi(mx));
                const bool cta_wide = it == 0 || it == LAST;
                if (cta_wide) {
                    sts64_if(lane < 2, sm + OFF_STAT + w * 16 + t * 8, n0, n1);
                    consumer_sync();
#pragma unroll
                    for (int i = 0; i < 8; i++) {
                        const float2 v = lds64f(sm + OFF_STAT + i * 16 + (t & 1) * 8);
                        if (t < 2) { n0 = fmaxf(n0, v.x); n1 = fmaxf(n1, v.y); }
                    }
                }
                if (__any_sync(~0u, n0 != m0 || n1 != m1)) {
                    const float c0 = ex2((m0 - n0) * LOG2E), c1 = ex2((m1 - n1) * LOG2E);
                    l0 *= c0;
                    l1 *= c1;
#pragma unroll
                    for (int i = 0; i < 8; i++) { o[i][0] *= c0; o[i][1] *= c1; o[i][2] *= c0; o[i][3] *= c1; }
                    m0 = n0;
                    m1 = n1;
                }
                const float p0 = ex2((bf_lo(sa) - m0) * LOG2E), p1 = ex2((bf_hi(sa) - m1) * LOG2E);
                const float p2 = ex2((bf_lo(sb) - m0) * LOG2E), p3 = ex2((bf_hi(sb) - m1) * LOG2E);
                l0 += p0 + p2;
                l1 += p1 + p3;
                const uint32_t pb0 = transpose8x8(pack_bf16(p0, p1)), pb1 = transpose8x8(pack_bf16(p2, p3));
                if (it == LAST) {
                    const float e0 = ex2((bf_lo(sa_prev) - m0) * LOG2E), e1 = ex2((bf_hi(sa_prev) - m1) * LOG2E);
                    const float e2 = ex2((bf_lo(sb_prev) - m0) * LOG2E), e3 = ex2((bf_hi(sb_prev) - m1) * LOG2E);
                    sts64(sm + OFF_P + tid * 8, transpose8x8(pack_bf16(e0, e1)), transpose8x8(pack_bf16(e2, e3)));
                    sts64(sm + OFF_P + 2048 + tid * 8, pb0, pb1);
                    float r0 = l0 + (e0 + e2), r1 = l1 + (e1 + e3);
#pragma unroll
                    for (int off = 4; off < 32; off <<= 1) {
                        r0 += __shfl_xor_sync(~0u, r0, off);
                        r1 += __shfl_xor_sync(~0u, r1, off);
                    }
                    sts64_if(lane < 2, sm + OFF_STAT + 128 + w * 16 + t * 8, r0, r1);
                    break;
                }

                mbar_wait(bar_full + 8 * slot, phase);
                {
                    const uint32_t base = sm + slot * STAGE + v_off;
#pragma unroll
                    for (int i = 0; i < 8; i++) {
                        uint32_t a[4];
                        ldsm4t(a, base + (i >> 2) * 8192 + ((((i & 3) * 2 + v_sel) ^ sw) << 4));
                        mma(o[i], a[0], a[1], a[2], a[3], pb0, pb1);
                    }
                }
                __syncwarp();
                if (lane == 0) mbar_arrive(bar_empty + 8 * slot);
                slot += 2;
                if (slot >= NSLOT) { slot -= NSLOT; phase ^= 1; }
            }
        }

        {
            constexpr int RED = ((4 * LAST) % NSLOT) * STAGE;
            const uint32_t on = live && t < 2;
#pragma unroll
            for (int i = 0; i < 8; i++) {
                const uint32_t a = sm + RED + w * 2048 + (i * 16 + g) * 16 + t * 8;
                sts64_if(on, a, o[i][0], o[i][1]);
                sts64_if(on, a + 128, o[i][2], o[i][3]);
            }
            consumer_sync();
            if (w == 0) {
                float L0 = 0.f, L1 = 0.f;
#pragma unroll
                for (int i = 0; i < 8; i++) {
                    const float2 v = lds64f(sm + OFF_STAT + 128 + i * 16 + (t & 1) * 8);
                    L0 += v.x;
                    L1 += v.y;
                }
                put2(live && lane < 2, stat_dst, m0, L0, tag);
                put2(live && lane < 2, stat_dst + 8 * 4, m1, L1, tag);
            }
            float c[4][4] = {};
            uint2 pf[16];
#pragma unroll
            for (int i = 0; i < 8; i++) {
                const float2 v = lds64f(sm + RED + i * 2048 + (w * 16 + g + (t >> 1) * 8) * 16 + (t & 1) * 8);
                c[0][0] += v.x;
                c[0][1] += v.y;
                pf[i] = lds64(sm + OFF_P + i * 256 + lane * 8);
                pf[i + 8] = lds64(sm + OFF_P + 2048 + i * 256 + lane * 8);
            }
            c[0][2] = __shfl_xor_sync(~0u, c[0][0], 2);
            c[0][3] = __shfl_xor_sync(~0u, c[0][1], 2);
            const uint32_t a_off = sm + (w >> 2) * 8192 + (sw + k_sel * 8) * 128 + ((((w & 3) * 2 + v_sel) ^ sw) << 4);
#pragma unroll
            for (int i = 0; i < 16; i++) {
                const int item = KV_ITEMS - 4 + i / 4;
                if (i % 4 == 0 && live) mbar_wait(bar_full + 8 * (item % NSLOT), (item / NSLOT) & 1);
                uint32_t a[4];
                ldsm4t(a, a_off + (item % NSLOT) * STAGE + (i % 4) * 2048);
                mma(c[i % 4], a[0], a[1], a[2], a[3], pf[i].x, pf[i].y);
            }
#pragma unroll
            for (int j = 0; j < 4; j++)
                put1(on, opart_dst + (j & 1) * 8 * 2 * 128 + (j >> 1) * 8, (c[0][j] + c[1][j]) + (c[2][j] + c[3][j]), tag);
        }

        uint4 dp = make_uint4(tag, tag, tag, tag);
        get1(live && w == 0, dp.x, down_src);
        get1(live && w == 0, dp.y, down_src + DM * 8);
        get1(live && w == 0, dp.z, down_src + 2 * DM * 8);
        get1(live && w == 0, dp.w, down_src + 3 * DM * 8);

        {
            const uint4 ready = make_uint4(tag, tag, tag, tag);
            uint4 st = ready, ua = ready, ub = ready;
            const uint32_t* src = g_opart + (head * 8 + w) * 256 + lane * 4;
            uint32_t spins = 0, want_st = live, want_a = live, want_b = live, want_w = 1;
            float wa, wb;
            uint32_t a[8][4];
            const uint32_t a_off = sm + OFF_W + (w >> 2) * 16384 + (sw + k_sel * 8) * 128 + ((((w & 3) * 2 + v_sel) ^ sw) << 4);
            do {
                get4(want_st, st, g_stat + (head * 8 + w) * 4);
                get4(want_a, ua, src);
                get4(want_b, ub, src + 128);
                const float ma = __uint_as_float(st.x & ~3u), mb = __uint_as_float(st.z & ~3u);
                const float mm = fmaxf(ma, mb);
                wa = ex2((ma - mm) * LOG2E);
                wb = ex2((mb - mm) * LOG2E);
                const float inv = rcp(wa * __uint_as_float(st.y) + wb * __uint_as_float(st.w));
                wa *= inv;
                wb *= inv;
                asm volatile("" : "+f"(wa), "+f"(wb));
                if (want_w && __all_sync(~0u, !live || mbar_test(bar_wo, 0))) {
                    want_w = 0;
#pragma unroll
                    for (int k = 0; k < 8; k++) ldsm4t(a[k], a_off + k * 2048);
                }
                want_st = stale(st, tag);
                want_a = stale(ua, tag);
                want_b = stale(ub, tag);
                if (++spins > SPIN_LIMIT) __trap();
            } while (__any_sync(~0u, want_st | want_a | want_b | want_w));
            sts64(sm + OFF_O + w * O_STRIDE + lane * 8,
                  pack_bf16(wa * __uint_as_float(ua.x) + wb * __uint_as_float(ub.x), wa * __uint_as_float(ua.y) + wb * __uint_as_float(ub.y)),
                  pack_bf16(wa * __uint_as_float(ua.z) + wb * __uint_as_float(ub.z), wa * __uint_as_float(ua.w) + wb * __uint_as_float(ub.w)));
            consumer_sync();
            float c[4][4] = {};
#pragma unroll
            for (int k = 0; k < 4; k++) {
                uint32_t b[4];
                ldsm4(b, sm + OFF_O + sw * O_STRIDE + (lane >> 3) * 16 + k * 64);
                mma(c[(k & 1) * 2], a[2 * k][0], a[2 * k][1], a[2 * k][2], a[2 * k][3], b[0], b[1]);
                mma(c[(k & 1) * 2 + 1], a[2 * k + 1][0], a[2 * k + 1][1], a[2 * k + 1][2], a[2 * k + 1][3], b[2], b[3]);
            }
            put2(live, part_dst, (c[0][0] + c[1][0]) + (c[2][0] + c[3][0]), (c[0][1] + c[1][1]) + (c[2][1] + c[3][1]), tag);
            put2(live, part_dst + 16, (c[0][2] + c[1][2]) + (c[2][2] + c[3][2]), (c[0][3] + c[1][3]) + (c[2][3] + c[3][3]), tag);
        }

        float gate;
        {
            uint32_t spins = 0;
            while (stale(dp, tag)) {
                get1(1, dp.x, down_src);
                get1(1, dp.y, down_src + DM * 8);
                get1(1, dp.z, down_src + 2 * DM * 8);
                get1(1, dp.w, down_src + 3 * DM * 8);
                if (++spins > SPIN_LIMIT) __trap();
            }
            const float d = round_bf16((__uint_as_float(dp.x) + __uint_as_float(dp.y)) + (__uint_as_float(dp.z) + __uint_as_float(dp.w)));
            gate = round_bf16(d * sigmoid(d));
        }

        {
            const uint32_t* src = g_part + (((w * 4 + (lane >> 3)) * 4 + (cta & 3)) * DM + (cta >> 2) * 16) * 2 + (lane & 7) * 4;
            uint4 u = make_uint4(tag, tag, tag, tag);
            uint32_t pending = live, spins = 0;
            do {
                get4(pending, u, src);
                pending = stale(u, tag);
                if (++spins > SPIN_LIMIT) __trap();
            } while (pending);
            __syncwarp();
            const bool up = lane & 16, b3 = lane & 8;
            const float a0 = __uint_as_float(up ? u.z : u.x) + __shfl_xor_sync(~0u, __uint_as_float(up ? u.x : u.z), 16);
            const float a1 = __uint_as_float(up ? u.w : u.y) + __shfl_xor_sync(~0u, __uint_as_float(up ? u.y : u.w), 16);
            const float r = (b3 ? a1 : a0) + __shfl_xor_sync(~0u, b3 ? a0 : a1, 8);
            sts32(sm + OFF_P + w * 128 + ((lane & 7) * 4 + (lane >> 4) * 2 + ((lane >> 3) & 1)) * 4, __float_as_uint(r));
            consumer_sync();
            if (w == 0) {
                float v[8];
#pragma unroll
                for (int i = 0; i < 8; i++) v[i] = __uint_as_float(lds32(sm + OFF_P + i * 128 + lane * 4));
                const float sv = round_bf16(((v[0] + v[1]) + (v[2] + v[3])) + ((v[4] + v[5]) + (v[6] + v[7])));
                const uint32_t res = pack_bf16(x_res + round_bf16(sv * gate), 0.f);
                asm volatile("{\n.reg .pred p;\n.reg .b16 lo, hi;\nsetp.ne.u32 p, %0, 0;\nmov.b32 {lo, hi}, %2;\n@p st.global.b16 [%1], lo;\n}"
                             ::"r"(live), "l"(out + out_batch * DM + out_col), "r"(res) : "memory");
                if (live && lane == 0) g_epoch[cta] = epoch;
            }
        }
        if (live) break;
    }
}

using EncodeFn = CUresult (*)(CUtensorMap*, CUtensorMapDataType, cuuint32_t, void*, const cuuint64_t*, const cuuint64_t*,
                              const cuuint32_t*, const cuuint32_t*, CUtensorMapInterleave, CUtensorMapSwizzle,
                              CUtensorMapL2promotion, CUtensorMapFloatOOBfill);

void encode(EncodeFn fn, CUtensorMap* m, void* p, cuuint64_t rows, cuuint64_t cols, cuuint32_t box_rows, cuuint32_t box_cols,
            cuuint32_t width = 64) {
    const cuuint64_t dims[3] = {width, rows, cols / width}, strides[2] = {cols * 2, width * 2};
    const cuuint32_t box[3] = {width, box_rows, box_cols / width}, elem[3] = {1, 1, 1};
    fn(m, CU_TENSOR_MAP_DATA_TYPE_BFLOAT16, 3, p, dims, strides, box, elem, CU_TENSOR_MAP_INTERLEAVE_NONE,
       width == 64 ? CU_TENSOR_MAP_SWIZZLE_128B : CU_TENSOR_MAP_SWIZZLE_64B, CU_TENSOR_MAP_L2_PROMOTION_L2_256B,
       CU_TENSOR_MAP_FLOAT_OOB_FILL_NONE);
}

}

extern "C" void kernel_launch(void* const* d_in, const int* in_sizes, int n_in, void* d_out, int out_size) {
    (void)in_sizes; (void)n_in; (void)out_size;
    static EncodeFn fn = nullptr;
    if (!fn) {
        cudaDriverEntryPointQueryResult status;
        cudaGetDriverEntryPoint("cuTensorMapEncodeTiled", (void**)&fn, cudaEnableDefault, &status);
        cudaFuncSetAttribute(decode_kernel, cudaFuncAttributeMaxDynamicSharedMemorySize, SMEM_BYTES);
    }
    Maps maps;
    encode(fn, &maps.m[MAP_K], d_in[1], 8 * 8 * 4096, 128, 64, 128);
    encode(fn, &maps.m[MAP_V], d_in[2], 8 * 8 * 4096, 128, 64, 128);
    encode(fn, &maps.m[MAP_WQ], d_in[3], DM, 4096, 256, 32, 32);
    encode(fn, &maps.m[MAP_WO], d_in[4], 4096, DM, 128, 128);
    encode(fn, &maps.m[MAP_WG], d_in[6], DM, FF, 16, FF_SLICE);
    encode(fn, &maps.m[MAP_WU], d_in[7], DM, FF, 16, FF_SLICE);
    encode(fn, &maps.m[MAP_WD], d_in[8], FF, DM, 16, DM);
    decode_kernel<<<GRID, N_THREADS, SMEM_BYTES>>>(maps, (const __nv_bfloat16*)d_in[0], (__nv_bfloat16*)d_out);
}
```

```cpp
#include <cuda.h>
#include <cuda_bf16.h>
#include <cuda_runtime.h>
#include <stdint.h>

namespace {

constexpr int DM = 512, FF = 1792;
constexpr int N_ATT = 128, N_FFN = 4, GRID = N_ATT + N_FFN;
constexpr int N_THREADS = 320;
constexpr int STAGE = 16384, NSLOT = 10;
constexpr int KV_ITEMS = 64;
constexpr int LAST = KV_ITEMS / 8 - 1;
constexpr int FF_SLICE = FF / N_FFN;
constexpr int GU_ITEMS = 2 * DM / 16;
constexpr int FFN_ITEMS = GU_ITEMS + FF_SLICE / 16;

constexpr int WIN_HEAD = 3, HEAD_ITEMS = 4, WIN_BODY = 4, WIN_FFN = 10;
constexpr int LAG_1 = 48, LAG_2 = 128, LEAD_1 = 160;
constexpr int TAIL_ITEMS = 8, WIN_TAIL = 10, WIN_TAIL_LEAD = 5, TAIL_LEAD = 192;
constexpr int GATE_LEFT = 680;
constexpr int RESET_STEP = 5;

constexpr int OFF_W = NSLOT * STAGE;
constexpr int H_STRIDE = 912;
constexpr int OFF_XN = OFF_W + 32768;
constexpr int XN_STRIDE = 1040;
constexpr int OFF_Q = OFF_XN + 8 * XN_STRIDE;
constexpr int OFF_O = OFF_Q + 4 * 272;
constexpr int O_STRIDE = 272;
constexpr int OFF_STAT = OFF_O + 8 * O_STRIDE;
constexpr int OFF_P = OFF_STAT + 256;
constexpr int OFF_BAR = OFF_P + 4096;
constexpr int OFF_CTL = OFF_BAR + 240;
constexpr int SMEM_BYTES = OFF_BAR + 256 + 1024;

constexpr float LOG2E = 1.4426950408889634f;
constexpr float QK_SCALE = 0.08838834764831845f;
constexpr uint32_t SPIN_LIMIT = 1u << 24;

enum { MAP_K, MAP_V, MAP_WQ, MAP_WG, MAP_WU, MAP_WD, MAP_WO, N_MAPS };
struct Maps { CUtensorMap m[N_MAPS]; };

__device__ uint32_t g_epoch[GRID];
__device__ uint32_t g_progress;
__device__ unsigned long long g_q[8 * 2048];
__device__ __align__(128) uint32_t g_opart[32 * 8 * 2 * 128];
__device__ __align__(128) uint32_t g_stat[32 * 8 * 4];
__device__ __align__(128) uint32_t g_part[32 * DM * 8];
__device__ __align__(128) uint32_t g_down[N_FFN * DM * 8];

__device__ __forceinline__ void mbar_init(uint32_t bar, uint32_t count) {
    asm volatile("mbarrier.init.shared::cta.b64 [%0], %1;" ::"r"(bar), "r"(count) : "memory");
}
__device__ __forceinline__ void mbar_expect_tx(uint32_t bar, uint32_t bytes) {
    asm volatile("mbarrier.arrive.expect_tx.shared::cta.b64 _, [%0], %1;" ::"r"(bar), "r"(bytes) : "memory");
}
__device__ __forceinline__ void mbar_arrive(uint32_t bar) {
    asm volatile("mbarrier.arrive.shared::cta.b64 _, [%0];" ::"r"(bar) : "memory");
}
__device__ __forceinline__ uint32_t mbar_test(uint32_t bar, uint32_t parity) {
    uint32_t ok;
    asm volatile("{\n.reg .pred p;\nmbarrier.test_wait.parity.shared::cta.b64 p, [%1], %2;\nselp.u32 %0, 1, 0, p;\n}"
                 : "=r"(ok) : "r"(bar), "r"(parity) : "memory");
    return ok;
}
__device__ __forceinline__ void mbar_wait(uint32_t bar, uint32_t parity) {
    uint32_t ok, spins = 0;
    do {
        asm volatile("{\n.reg .pred p;\nmbarrier.try_wait.parity.shared::cta.b64 p, [%1], %2;\nselp.u32 %0, 1, 0, p;\n}"
                     : "=r"(ok) : "r"(bar), "r"(parity) : "memory");
        if (++spins > SPIN_LIMIT) __trap();
    } while (!ok);
}
__device__ __forceinline__ void tma_load(uint32_t dst, const CUtensorMap* m, int row, int block, uint32_t bar) {
    asm volatile("{\n.reg .b64 policy;\ncreatepolicy.fractional.L2::evict_first.b64 policy, 1.0;\n"
                 "cp.async.bulk.tensor.3d.shared::cluster.global.mbarrier::complete_tx::bytes.L2::cache_hint [%0], [%1, {%3, %4, %5}], [%2], policy;\n}"
                 ::"r"(dst), "l"(m), "r"(bar), "r"(0), "r"(row), "r"(block) : "memory");
}
__device__ __forceinline__ void consumer_sync() { asm volatile("bar.sync 1, 256;" ::: "memory"); }
__device__ __forceinline__ void ldsm4(uint32_t (&r)[4], uint32_t addr) {
    asm volatile("ldmatrix.sync.aligned.m8n8.x4.shared.b16 {%0,%1,%2,%3}, [%4];"
                 : "=r"(r[0]), "=r"(r[1]), "=r"(r[2]), "=r"(r[3]) : "r"(addr) : "memory");
}
__device__ __forceinline__ void ldsm4t(uint32_t (&r)[4], uint32_t addr) {
    asm volatile("ldmatrix.sync.aligned.m8n8.x4.trans.shared.b16 {%0,%1,%2,%3}, [%4];"
                 : "=r"(r[0]), "=r"(r[1]), "=r"(r[2]), "=r"(r[3]) : "r"(addr) : "memory");
}
__device__ __forceinline__ void mma(float (&c)[4], uint32_t a0, uint32_t a1, uint32_t a2, uint32_t a3, uint32_t b0, uint32_t b1) {
    asm volatile("mma.sync.aligned.m16n8k16.row.col.f32.bf16.bf16.f32 {%0,%1,%2,%3}, {%4,%5,%6,%7}, {%8,%9}, {%0,%1,%2,%3};"
                 : "+f"(c[0]), "+f"(c[1]), "+f"(c[2]), "+f"(c[3])
                 : "r"(a0), "r"(a1), "r"(a2), "r"(a3), "r"(b0), "r"(b1));
}
__device__ __forceinline__ uint32_t transpose8x8(uint32_t a) {
    uint32_t d;
    asm volatile("movmatrix.sync.aligned.m8n8.trans.b16 %0, %1;" : "=r"(d) : "r"(a));
    return d;
}
__device__ __forceinline__ uint32_t pack_bf16(float lo, float hi) {
    uint32_t d;
    asm("cvt.rn.bf16x2.f32 %0, %1, %2;" : "=r"(d) : "f"(hi), "f"(lo));
    return d;
}
__device__ __forceinline__ float bf_lo(uint32_t v) { return __uint_as_float(v << 16); }
__device__ __forceinline__ float bf_hi(uint32_t v) { return __uint_as_float(v & 0xffff0000u); }
__device__ __forceinline__ float round_bf16(float v) { return bf_lo(pack_bf16(v, 0.f)); }
__device__ __forceinline__ uint32_t max_bf16x2(uint32_t a, uint32_t b) {
    uint32_t d;
    asm("max.bf16x2 %0, %1, %2;" : "=r"(d) : "r"(a), "r"(b));
    return d;
}
__device__ __forceinline__ float ex2(float x) {
    float y;
    asm("ex2.approx.ftz.f32 %0, %1;" : "=f"(y) : "f"(x));
    return y;
}
__device__ __forceinline__ float rcp(float x) {
    float y;
    asm("rcp.approx.ftz.f32 %0, %1;" : "=f"(y) : "f"(x));
    return y;
}
__device__ __forceinline__ float sqrt_approx(float x) {
    float y;
    asm("sqrt.approx.ftz.f32 %0, %1;" : "=f"(y) : "f"(x));
    return y;
}
__device__ __forceinline__ float sigmoid(float x) { return rcp(1.f + ex2(-x * LOG2E)); }
__device__ __forceinline__ void sts32(uint32_t addr, uint32_t v) { asm volatile("st.shared.b32 [%0], %1;" ::"r"(addr), "r"(v) : "memory"); }
__device__ __forceinline__ void sts64(uint32_t addr, uint32_t a, uint32_t b) { asm volatile("st.shared.v2.b32 [%0], {%1,%2};" ::"r"(addr), "r"(a), "r"(b) : "memory"); }
__device__ __forceinline__ uint32_t lds32(uint32_t addr) {
    uint32_t v;
    asm volatile("ld.shared.b32 %0, [%1];" : "=r"(v) : "r"(addr) : "memory");
    return v;
}
__device__ __forceinline__ uint2 lds64(uint32_t addr) {
    uint2 v;
    asm volatile("ld.shared.v2.b32 {%0,%1}, [%2];" : "=r"(v.x), "=r"(v.y) : "r"(addr) : "memory");
    return v;
}
__device__ __forceinline__ float2 lds64f(uint32_t addr) {
    float2 v;
    asm volatile("ld.shared.v2.f32 {%0,%1}, [%2];" : "=f"(v.x), "=f"(v.y) : "r"(addr) : "memory");
    return v;
}

__device__ __forceinline__ void sts64_if(uint32_t on, uint32_t addr, float a, float b) {
    asm volatile("{\n.reg .pred p;\nsetp.ne.u32 p, %0, 0;\n@p st.shared.v2.f32 [%1], {%2,%3};\n}" ::"r"(on), "r"(addr), "f"(a), "f"(b) : "memory");
}

__device__ __forceinline__ void put_pair(unsigned long long* p, uint32_t data, uint32_t epoch) {
    asm volatile("st.relaxed.gpu.global.b64 [%0], %1;" ::"l"(p), "l"(((unsigned long long)epoch << 32) | data) : "memory");
}
__device__ __forceinline__ uint32_t get_pair(const unsigned long long* p, uint32_t epoch) {
    unsigned long long v;
    uint32_t spins = 0;
    do {
        asm volatile("ld.relaxed.gpu.global.b64 %0, [%1];" : "=l"(v) : "l"(p) : "memory");
        if (++spins > SPIN_LIMIT) __trap();
    } while ((uint32_t)(v >> 32) != epoch);
    return (uint32_t)v;
}
__device__ __forceinline__ uint32_t tagged(float v, uint32_t tag) { return (__float_as_uint(v) & ~3u) | tag; }
__device__ __forceinline__ void put1(uint32_t on, uint32_t* p, float a, uint32_t tag) {
    asm volatile("{\n.reg .pred p;\nsetp.ne.u32 p, %0, 0;\n@p st.relaxed.gpu.global.b32 [%1], %2;\n}" ::"r"(on), "l"(p), "r"(tagged(a, tag)) : "memory");
}
__device__ __forceinline__ void put2(uint32_t on, uint32_t* p, float a, float b, uint32_t tag) {
    asm volatile("{\n.reg .pred p;\nsetp.ne.u32 p, %0, 0;\n@p st.relaxed.gpu.global.v2.b32 [%1], {%2,%3};\n}"
                 ::"r"(on), "l"(p), "r"(tagged(a, tag)), "r"(tagged(b, tag)) : "memory");
}
__device__ __forceinline__ void get1(uint32_t on, uint32_t& v, const uint32_t* p) {
    asm volatile("{\n.reg .pred p;\nsetp.ne.u32 p, %2, 0;\n@p ld.relaxed.gpu.global.b32 %0, [%1];\n}" : "+r"(v) : "l"(p), "r"(on) : "memory");
}
__device__ __forceinline__ void get4(uint32_t on, uint4& v, const uint32_t* p) {
    asm volatile("{\n.reg .pred p;\nsetp.ne.u32 p, %5, 0;\n@p ld.relaxed.gpu.global.v4.b32 {%0,%1,%2,%3}, [%4];\n}"
                 : "+r"(v.x), "+r"(v.y), "+r"(v.z), "+r"(v.w) : "l"(p), "r"(on) : "memory");
}
__device__ __forceinline__ uint32_t stale(const uint4& v, uint32_t tag) {
    return ((v.x ^ tag) | (v.y ^ tag) | (v.z ^ tag) | (v.w ^ tag)) & 3u;
}

__device__ __forceinline__ void layernorm_row(const uint4& u0, const uint4& u1, int lane, uint32_t xn_row) {
    const uint32_t u[8] = {u0.x, u0.y, u0.z, u0.w, u1.x, u1.y, u1.z, u1.w};
    float v[16], sum = 0.f;
#pragma unroll
    for (int i = 0; i < 8; i++) { v[2 * i] = bf_lo(u[i]); v[2 * i + 1] = bf_hi(u[i]); sum += v[2 * i] + v[2 * i + 1]; }
#pragma unroll
    for (int o = 16; o > 0; o >>= 1) sum += __shfl_xor_sync(~0u, sum, o);
    const float mean = sum * (1.f / DM);
    float sq = 0.f;
#pragma unroll
    for (int i = 0; i < 16; i++) sq += (v[i] - mean) * (v[i] - mean);
#pragma unroll
    for (int o = 16; o > 0; o >>= 1) sq += __shfl_xor_sync(~0u, sq, o);
    const float mean_b = round_bf16(mean);
    const float inv = rcp(round_bf16(sqrt_approx(round_bf16(round_bf16(sq * (1.f / DM)) + 1e-5f))));
    uint32_t r[8];
#pragma unroll
    for (int i = 0; i < 8; i++) r[i] = pack_bf16(round_bf16(v[2 * i] - mean_b) * inv, round_bf16(v[2 * i + 1] - mean_b) * inv);
    asm volatile("st.shared.v4.b32 [%0], {%1,%2,%3,%4};" ::"r"(xn_row + lane * 16), "r"(r[0]), "r"(r[1]), "r"(r[2]), "r"(r[3]) : "memory");
    asm volatile("st.shared.v4.b32 [%0], {%1,%2,%3,%4};" ::"r"(xn_row + 512 + lane * 16), "r"(r[4]), "r"(r[5]), "r"(r[6]), "r"(r[7]) : "memory");
}

__global__ void __launch_bounds__(N_THREADS, 1)
decode_kernel(const __grid_constant__ Maps maps, const __nv_bfloat16* __restrict__ x, __nv_bfloat16* __restrict__ out) {
    extern __shared__ __align__(1024) unsigned char smem_raw[];
    const uint32_t sm = ((uint32_t)__cvta_generic_to_shared(smem_raw) + 1023u) & ~1023u;
    const uint32_t bar_wq = sm + OFF_BAR, bar_full = bar_wq + 16, bar_wo = bar_full + 8 * NSLOT, bar_empty = bar_wo + 8;
    const int tid = threadIdx.x, w = tid >> 5, lane = tid & 31;
    const int cta = blockIdx.x;
    const bool att = cta < N_ATT;

    if (__builtin_expect(tid == 256 && att, 1)) {
#pragma unroll
        for (int i = 0; i < 3; i++) mbar_init(bar_wq + 8 * i, 1);
        asm volatile("fence.proxy.async.shared::cta;" ::: "memory");
#pragma unroll
        for (int i = 0; i < 2; i++) {
            mbar_expect_tx(bar_wq + 8 * i, STAGE);
            tma_load(sm + OFF_W + i * STAGE, &maps.m[MAP_WQ], i * 256, cta, bar_wq + 8 * i);
        }
        mbar_expect_tx(bar_full, STAGE);
        tma_load(sm, &maps.m[MAP_K], cta * 2048, 0, bar_full);
    }

    if (w == 8) {
        __syncwarp();
        asm volatile("bar.arrive 0, 320;" ::: "memory");
        asm volatile("bar.sync 2, 64;" ::: "memory");
        if (lane != 0) return;
        const int n_ring = att ? KV_ITEMS : FFN_ITEMS;
        int landed = att ? -2 : 0, slot = att ? 1 : 0, lslot = 0;
        uint32_t phase = 1, lphase = 0;
        auto count_landed = [&]() {
            if (landed >= 0) {
                if (++lslot == NSLOT) { lslot = 0; lphase ^= 1; }
                if (att) asm volatile("red.relaxed.gpu.global.add.u32 [%0], 1;" ::"l"(&g_progress) : "memory");
            }
            landed++;
        };
#pragma unroll 1
        for (int n = slot; n < n_ring; n++) {
            int win = WIN_FFN;
            if (att) {
                const int lead = N_ATT * landed - (int)lds32(sm + OFF_CTL);
                win = WIN_BODY + (lead < -LAG_1) + (lead < -LAG_2) - (lead > LEAD_1);
                if (n < HEAD_ITEMS) win = WIN_HEAD;
                if (n >= KV_ITEMS - TAIL_ITEMS) win = lead > TAIL_LEAD ? WIN_TAIL_LEAD : WIN_TAIL;
            }
#pragma unroll 1
            while (landed <= n - win || (landed < n && mbar_test(bar_full + 8 * (landed < 0 ? landed : lslot), lphase))) {
                mbar_wait(bar_full + 8 * (landed < 0 ? landed : lslot), lphase);
                count_landed();
            }
            mbar_wait(bar_empty + 8 * slot, phase);
            const uint32_t bar = bar_full + 8 * slot;
            mbar_expect_tx(bar, att || n >= GU_ITEMS ? STAGE : 32 * FF_SLICE);
            int map = MAP_K + ((n >> 2) & 1), row = cta * 2048 + (n >> 3) * 256 + (n & 3) * 64, block = 0;
            if (!att) {
                const bool gu = n < GU_ITEMS;
                map = gu ? MAP_WG + (n & 1) : MAP_WD;
                row = gu ? (n >> 1) * 16 : (cta - N_ATT) * FF_SLICE + (n - GU_ITEMS) * 16;
                block = gu ? (cta - N_ATT) * (FF_SLICE / 64) : 0;
            }
            tma_load(sm + slot * STAGE, &maps.m[map], row, block, bar);
            if (++slot == NSLOT) { slot = 0; phase ^= 1; }
        }
        if (att) {
            uint32_t spins = 0;
            bool gated = true;
#pragma unroll 1
            while (gated || landed < KV_ITEMS) {
                if (landed < KV_ITEMS && mbar_test(bar_full + 8 * lslot, lphase)) count_landed();
                if (gated && (int)lds32(sm + OFF_CTL) >= N_ATT * KV_ITEMS - GATE_LEFT) {
                    gated = false;
                    mbar_expect_tx(bar_wo, 32768);
                    tma_load(sm + OFF_W, &maps.m[MAP_WO], (cta >> 2) * 128, (cta & 3) * 2, bar_wo);
                    sts32(sm + OFF_CTL + 4, 1);
                }
                if (++spins > SPIN_LIMIT) __trap();
            }
        }
        return;
    }
    if (w == 9) {
        if (lane == 0) {
#pragma unroll
            for (int i = 0; i < 2 * NSLOT + 3; i++)
                if (i >= 3 || !att) mbar_init(bar_wq + 8 * i, i < NSLOT + 3 ? 1 : att ? 4 : 8);
            sts64(sm + OFF_CTL, 0, 0);
            asm volatile("fence.proxy.async.shared::cta;" ::: "memory");
        }
        __syncwarp();
        asm volatile("bar.arrive 2, 64;" ::: "memory");
        asm volatile("bar.arrive 0, 320;" ::: "memory");
        if (lane == 0 && att) {
            uint32_t base, spins = 0;
            asm volatile("ld.relaxed.gpu.global.b32 %0, [%1];" : "=r"(base) : "l"(g_epoch + cta) : "memory");
            base *= N_ATT * KV_ITEMS;
            while (!lds32(sm + OFF_CTL + 4) && ++spins < SPIN_LIMIT) {
                uint32_t v;
                asm volatile("ld.relaxed.gpu.global.b32 %0, [%1];" : "=r"(v) : "l"(&g_progress) : "memory");
                sts32(sm + OFF_CTL, v - base);
            }
        }
        return;
    }

    const uint4* xr = reinterpret_cast<const uint4*>(x + w * DM);
    const uint4 xa = __ldg(xr + lane), xb = __ldg(xr + 32 + lane);
    uint32_t epoch;
    asm volatile("ld.relaxed.gpu.global.b32 %0, [%1];" : "=r"(epoch) : "l"(g_epoch + cta) : "memory");
    const int g = lane >> 2, t = lane & 3;
    const int out_batch = (cta & 3) * 2 + (lane & 1), out_col = (cta >> 2) * 16 + (lane >> 1);
    float x_res = 0.f;
    if (att && w == 0) x_res = __bfloat162float(__ldg(x + out_batch * DM + out_col));
    layernorm_row(xa, xb, lane, sm + OFF_XN + w * XN_STRIDE);
    epoch += 1;
    const uint32_t tag = epoch & 3u;
    asm volatile("bar.sync 0, 320;" ::: "memory");
    const uint32_t xn_addr = sm + OFF_XN + (lane & 7) * XN_STRIDE + (lane >> 3) * 16;
    const int sw = lane & 7;
    const int k_sel = lane >> 4, v_sel = (lane >> 3) & 1;

    if (!att) {
        int slot = 0;
        uint32_t phase = 0;
        float acc[2][7][4] = {};
#pragma unroll 1
        for (int k = 0; k < DM / 16; k++) {
            uint32_t a[4];
            ldsm4(a, xn_addr + k * 32);
#pragma unroll
            for (int u = 0; u < 2; u++) {
                mbar_wait(bar_full + 8 * slot, phase);
#pragma unroll
                for (int j = 0; j < 7; j += 2) {
                    uint32_t b[4];
                    ldsm4t(b, sm + slot * STAGE + j * 2048 + lane * 128 + ((w ^ sw) << 4));
                    mma(acc[u][j], a[0], 0, a[1], 0, b[0], b[1]);
                    if (j < 6) mma(acc[u][j + 1], a[0], 0, a[1], 0, b[2], b[3]);
                }
                __syncwarp();
                if (lane == 0) mbar_arrive(bar_empty + 8 * slot);
                if (++slot == NSLOT) { slot = 0; phase ^= 1; }
            }
        }
#pragma unroll
        for (int j = 0; j < 7; j++)
            sts32(sm + OFF_W + g * H_STRIDE + j * 128 + w * 16 + t * 4,
                  pack_bf16(round_bf16(sigmoid(round_bf16(acc[0][j][0]))) * round_bf16(acc[1][j][0]),
                            round_bf16(sigmoid(round_bf16(acc[0][j][1]))) * round_bf16(acc[1][j][1])));
        consumer_sync();
        float c[4][4] = {};
#pragma unroll 1
        for (int k = 0; k < FF_SLICE / 16; k++) {
            uint32_t b[4];
            ldsm4(b, sm + OFF_W + sw * H_STRIDE + (lane >> 3) * 16 + k * 32);
            mbar_wait(bar_full + 8 * slot, phase);
#pragma unroll
            for (int j = 0; j < 4; j++) {
                uint32_t a[4];
                ldsm4t(a, sm + slot * STAGE + w * 2048 + (sw + k_sel * 8) * 128 + (((j * 2 + v_sel) ^ sw) << 4));
                mma(c[j], a[0], a[1], a[2], a[3], b[0], b[1]);
            }
            __syncwarp();
            if (lane == 0) mbar_arrive(bar_empty + 8 * slot);
            if (++slot == NSLOT) { slot = 0; phase ^= 1; }
        }
#pragma unroll
        for (int j = 0; j < 4; j++) {
            uint32_t* dst = g_down + ((cta - N_ATT) * DM + w * 64 + j * 16 + g) * 8 + t * 2;
            put2(1, dst, c[j][0], c[j][1], tag);
            put2(1, dst + 64, c[j][2], c[j][3], tag);
        }
        if (tid == 0) g_epoch[cta] = epoch;
        return;
    }

    const int batch = cta >> 4, hkv = (cta >> 1) & 7, half = cta & 1;

    if (w < 4) {
        float acc[2][4] = {};
        const uint32_t b_addr = sm + OFF_W + lane * 64 + ((w ^ ((lane >> 1) & 3)) << 4);
#pragma unroll 1
        for (int kh = 0; kh < 4; kh++) {
            mbar_wait(bar_wq + (kh >> 1) * 8, 0);
#pragma unroll
            for (int k = 0; k < 4; k++) {
                uint32_t a[4], b[4];
                ldsm4(a, xn_addr + kh * 256 + k * 64);
                ldsm4t(b, b_addr + kh * 8192 + k * 2048);
                mma(acc[0], a[0], 0, a[1], 0, b[0], b[1]);
                mma(acc[1], a[2], 0, a[3], 0, b[2], b[3]);
            }
        }
        put_pair(g_q + g * 2048 + cta * 16 + w * 4 + t, pack_bf16(acc[0][0] + acc[1][0], acc[0][1] + acc[1][1]), epoch);
    }

    float o[8][4] = {};
    float m0 = -INFINITY, m1 = -INFINITY;
    const int head = cta >> 2;
    uint32_t* const opart_dst = g_opart + (((hkv * 4 + (t & 1) * 2) * 8 + batch) * 2 + half) * 128 + w * 16 + g;
    uint32_t* const stat_dst = g_stat + (((hkv * 4 + (t & 1) * 2) * 8 + batch) * 2 + half) * 2;
    uint32_t* const part_dst = g_part + ((head * 4 + t) * DM + (cta & 3) * 128 + w * 16 + g) * 2;
    const uint32_t* const down_src = g_down + out_col * 8 + out_batch;

    uint32_t live;
    asm volatile("mov.u32 %0, 0;" : "=r"(live));
#pragma unroll 1
    for (;; live = 1) {
        if (live) {
            sts32(sm + OFF_Q + (tid >> 6) * 272 + (tid & 63) * 4, get_pair(g_q + batch * 2048 + hkv * 256 + tid, epoch));
            consumer_sync();
            uint32_t qf[8][2];
#pragma unroll
            for (int j = 0; j < 8; j++) {
                const uint32_t a = sm + OFF_Q + (g & 3) * 272 + j * 32 + t * 4;
                qf[j][0] = g < 4 ? lds32(a) : 0u;
                qf[j][1] = g < 4 ? lds32(a + 16) : 0u;
            }

            const uint32_t k_off = ((w & 3) * 16 + sw + v_sel * 8) * 128;
            const uint32_t v_off = ((w & 3) * 16 + sw + k_sel * 8) * 128;
            float l0 = 0.f, l1 = 0.f;
            auto reset_exchange = [&]() {
                const uint32_t none = tag ^ 2u;
                put1(1, opart_dst + (t >> 1) * 8, 0.f, none);
                put1(1, opart_dst + (t >> 1) * 8 + 8 * 2 * 128, 0.f, none);
                put2(tid < 2, stat_dst, 0.f, 0.f, none);
                put2(tid < 2, stat_dst + 8 * 4, 0.f, 0.f, none);
                put2(1, part_dst, 0.f, 0.f, none);
                put2(1, part_dst + 16, 0.f, 0.f, none);
            };
            int slot = w >> 2;
            uint32_t phase = 0;
#pragma unroll 1
            for (int it = 0;; it++) {
                uint32_t sa = 0, sb = 0, sa_prev, sb_prev, mx = 0xff80ff80u;
                if (it == RESET_STEP) reset_exchange();
#pragma unroll 1
                for (int r = 0; r < 2; r++) {
                    mbar_wait(bar_full + 8 * slot, phase);
                    float s[2][4] = {};
                    const uint32_t base = sm + slot * STAGE + k_off;
#pragma unroll
                    for (int j = 0; j < 8; j++) {
                        uint32_t a[4];
                        ldsm4(a, base + (j >> 2) * 8192 + ((((j & 3) * 2 + k_sel) ^ sw) << 4));
                        mma(s[j & 1], a[0], a[1], a[2], a[3], qf[j][0], qf[j][1]);
                    }
                    __syncwarp();
                    if (lane == 0) mbar_arrive(bar_empty + 8 * slot);
                    slot += 2;
                    if (slot >= NSLOT) { slot -= NSLOT; phase ^= 1; }
                    sa_prev = sa;
                    sb_prev = sb;
                    sa = pack_bf16(s[0][0] + s[1][0], s[0][1] + s[1][1]);
                    sb = pack_bf16(s[0][2] + s[1][2], s[0][3] + s[1][3]);
                    sa = pack_bf16(bf_lo(sa) * QK_SCALE, bf_hi(sa) * QK_SCALE);
                    sb = pack_bf16(bf_lo(sb) * QK_SCALE, bf_hi(sb) * QK_SCALE);
                    mx = max_bf16x2(mx, max_bf16x2(sa, sb));
                }
                mx = max_bf16x2(mx, __shfl_xor_sync(~0u, mx, 4));
                mx = max_bf16x2(mx, __shfl_xor_sync(~0u, mx, 8));
                mx = max_bf16x2(mx, __shfl_xor_sync(~0u, mx, 16));
                float n0 = fmaxf(m0, bf_lo(mx)), n1 = fmaxf(m1, bf_hi(mx));
                const bool cta_wide = it == 0 || it == LAST;
                if (cta_wide) {
                    sts64_if(lane < 2, sm + OFF_STAT + w * 16 + t * 8, n0, n1);
                    consumer_sync();
#pragma unroll
                    for (int i = 0; i < 8; i++) {
                        const float2 v = lds64f(sm + OFF_STAT + i * 16 + (t & 1) * 8);
                        if (t < 2) { n0 = fmaxf(n0, v.x); n1 = fmaxf(n1, v.y); }
                    }
                }
                if (__any_sync(~0u, n0 != m0 || n1 != m1)) {
                    const float c0 = ex2((m0 - n0) * LOG2E), c1 = ex2((m1 - n1) * LOG2E);
                    l0 *= c0;
                    l1 *= c1;
#pragma unroll
                    for (int i = 0; i < 8; i++) { o[i][0] *= c0; o[i][1] *= c1; o[i][2] *= c0; o[i][3] *= c1; }
                    m0 = n0;
                    m1 = n1;
                }
                const float p0 = ex2((bf_lo(sa) - m0) * LOG2E), p1 = ex2((bf_hi(sa) - m1) * LOG2E);
                const float p2 = ex2((bf_lo(sb) - m0) * LOG2E), p3 = ex2((bf_hi(sb) - m1) * LOG2E);
                l0 += p0 + p2;
                l1 += p1 + p3;
                const float e0 = ex2((bf_lo(sa_prev) - m0) * LOG2E), e1 = ex2((bf_hi(sa_prev) - m1) * LOG2E);
                const float e2 = ex2((bf_lo(sb_prev) - m0) * LOG2E), e3 = ex2((bf_hi(sb_prev) - m1) * LOG2E);
                l0 += e0 + e2;
                l1 += e1 + e3;
                uint32_t pb0 = transpose8x8(pack_bf16(e0, e1)), pb1 = transpose8x8(pack_bf16(e2, e3));
                const uint32_t pb2 = transpose8x8(pack_bf16(p0, p1)), pb3 = transpose8x8(pack_bf16(p2, p3));
                if (it == LAST) {
                    sts64(sm + OFF_P + tid * 8, pb0, pb1);
                    sts64(sm + OFF_P + 2048 + tid * 8, pb2, pb3);
                    float r0 = l0, r1 = l1;
#pragma unroll
                    for (int off = 4; off < 32; off <<= 1) {
                        r0 += __shfl_xor_sync(~0u, r0, off);
                        r1 += __shfl_xor_sync(~0u, r1, off);
                    }
                    sts64_if(lane < 2, sm + OFF_STAT + 128 + w * 16 + t * 8, r0, r1);
                    break;
                }

#pragma unroll 1
                for (int r = 0; r < 2; r++) {
                    mbar_wait(bar_full + 8 * slot, phase);
                    const uint32_t base = sm + slot * STAGE + v_off;
#pragma unroll
                    for (int i = 0; i < 8; i++) {
                        uint32_t a[4];
                        ldsm4t(a, base + (i >> 2) * 8192 + ((((i & 3) * 2 + v_sel) ^ sw) << 4));
                        mma(o[i], a[0], a[1], a[2], a[3], pb0, pb1);
                    }
                    __syncwarp();
                    if (lane == 0) mbar_arrive(bar_empty + 8 * slot);
                    slot += 2;
                    if (slot >= NSLOT) { slot -= NSLOT; phase ^= 1; }
                    pb0 = pb2;
                    pb1 = pb3;
                }
            }
        }

        {
            constexpr int RED = ((8 * LAST) % NSLOT) * STAGE;
            const uint32_t on = live && t < 2;
#pragma unroll
            for (int i = 0; i < 8; i++) {
                const uint32_t a = sm + RED + w * 2048 + (i * 16 + g) * 16 + t * 8;
                sts64_if(on, a, o[i][0], o[i][1]);
                sts64_if(on, a + 128, o[i][2], o[i][3]);
            }
            consumer_sync();
            if (w == 0) {
                float L0 = 0.f, L1 = 0.f;
#pragma unroll
                for (int i = 0; i < 8; i++) {
                    const float2 v = lds64f(sm + OFF_STAT + 128 + i * 16 + (t & 1) * 8);
                    L0 += v.x;
                    L1 += v.y;
                }
                put2(live && lane < 2, stat_dst, m0, L0, tag);
                put2(live && lane < 2, stat_dst + 8 * 4, m1, L1, tag);
            }
            float c[4][4] = {};
            uint2 pf[16];
#pragma unroll
            for (int i = 0; i < 8; i++) {
                const float2 v = lds64f(sm + RED + i * 2048 + (w * 16 + g + (t >> 1) * 8) * 16 + (t & 1) * 8);
                c[0][0] += v.x;
                c[0][1] += v.y;
                pf[i] = lds64(sm + OFF_P + i * 256 + lane * 8);
                pf[i + 8] = lds64(sm + OFF_P + 2048 + i * 256 + lane * 8);
            }
            c[0][2] = __shfl_xor_sync(~0u, c[0][0], 2);
            c[0][3] = __shfl_xor_sync(~0u, c[0][1], 2);
            const uint32_t a_off = sm + (w >> 2) * 8192 + (sw + k_sel * 8) * 128 + ((((w & 3) * 2 + v_sel) ^ sw) << 4);
#pragma unroll
            for (int i = 0; i < 16; i++) {
                const int item = KV_ITEMS - 4 + i / 4;
                if (i % 4 == 0 && live) mbar_wait(bar_full + 8 * (item % NSLOT), (item / NSLOT) & 1);
                uint32_t a[4];
                ldsm4t(a, a_off + (item % NSLOT) * STAGE + (i % 4) * 2048);
                mma(c[i % 4], a[0], a[1], a[2], a[3], pf[i].x, pf[i].y);
            }
#pragma unroll
            for (int j = 0; j < 4; j++)
                put1(on, opart_dst + (j & 1) * 8 * 2 * 128 + (j >> 1) * 8, (c[0][j] + c[1][j]) + (c[2][j] + c[3][j]), tag);
        }

        uint4 dp = make_uint4(tag, tag, tag, tag);
        get1(live && w == 0, dp.x, down_src);
        get1(live && w == 0, dp.y, down_src + DM * 8);
        get1(live && w == 0, dp.z, down_src + 2 * DM * 8);
        get1(live && w == 0, dp.w, down_src + 3 * DM * 8);

        {
            const uint4 ready = make_uint4(tag, tag, tag, tag);
            uint4 st = ready, ua = ready, ub = ready;
            const uint32_t* src = g_opart + (head * 8 + w) * 256 + lane * 4;
            uint32_t spins = 0, want_st = live, want_a = live, want_b = live, want_w = 1;
            float wa, wb;
            uint32_t a[8][4];
            const uint32_t a_off = sm + OFF_W + (w >> 2) * 16384 + (sw + k_sel * 8) * 128 + ((((w & 3) * 2 + v_sel) ^ sw) << 4);
            do {
                get4(want_st, st, g_stat + (head * 8 + w) * 4);
                get4(want_a, ua, src);
                get4(want_b, ub, src + 128);
                const float ma = __uint_as_float(st.x & ~3u), mb = __uint_as_float(st.z & ~3u);
                const float mm = fmaxf(ma, mb);
                wa = ex2((ma - mm) * LOG2E);
                wb = ex2((mb - mm) * LOG2E);
                const float inv = rcp(wa * __uint_as_float(st.y) + wb * __uint_as_float(st.w));
                wa *= inv;
                wb *= inv;
                asm volatile("" : "+f"(wa), "+f"(wb));
                if (want_w && __all_sync(~0u, !live || mbar_test(bar_wo, 0))) {
                    want_w = 0;
#pragma unroll
                    for (int k = 0; k < 8; k++) ldsm4t(a[k], a_off + k * 2048);
                }
                want_st = stale(st, tag);
                want_a = stale(ua, tag);
                want_b = stale(ub, tag);
                if (++spins > SPIN_LIMIT) __trap();
            } while (__any_sync(~0u, want_st | want_a | want_b | want_w));
            sts64(sm + OFF_O + w * O_STRIDE + lane * 8,
                  pack_bf16(wa * __uint_as_float(ua.x) + wb * __uint_as_float(ub.x), wa * __uint_as_float(ua.y) + wb * __uint_as_float(ub.y)),
                  pack_bf16(wa * __uint_as_float(ua.z) + wb * __uint_as_float(ub.z), wa * __uint_as_float(ua.w) + wb * __uint_as_float(ub.w)));
            consumer_sync();
            float c[4][4] = {};
#pragma unroll
            for (int k = 0; k < 4; k++) {
                uint32_t b[4];
                ldsm4(b, sm + OFF_O + sw * O_STRIDE + (lane >> 3) * 16 + k * 64);
                mma(c[(k & 1) * 2], a[2 * k][0], a[2 * k][1], a[2 * k][2], a[2 * k][3], b[0], b[1]);
                mma(c[(k & 1) * 2 + 1], a[2 * k + 1][0], a[2 * k + 1][1], a[2 * k + 1][2], a[2 * k + 1][3], b[2], b[3]);
            }
            put2(live, part_dst, (c[0][0] + c[1][0]) + (c[2][0] + c[3][0]), (c[0][1] + c[1][1]) + (c[2][1] + c[3][1]), tag);
            put2(live, part_dst + 16, (c[0][2] + c[1][2]) + (c[2][2] + c[3][2]), (c[0][3] + c[1][3]) + (c[2][3] + c[3][3]), tag);
        }

        float gate;
        {
            uint32_t spins = 0;
            while (stale(dp, tag)) {
                get1(1, dp.x, down_src);
                get1(1, dp.y, down_src + DM * 8);
                get1(1, dp.z, down_src + 2 * DM * 8);
                get1(1, dp.w, down_src + 3 * DM * 8);
                if (++spins > SPIN_LIMIT) __trap();
            }
            const float d = round_bf16((__uint_as_float(dp.x) + __uint_as_float(dp.y)) + (__uint_as_float(dp.z) + __uint_as_float(dp.w)));
            gate = round_bf16(d * sigmoid(d));
        }

        {
            const uint32_t* src = g_part + (((w * 4 + (lane >> 3)) * 4 + (cta & 3)) * DM + (cta >> 2) * 16) * 2 + (lane & 7) * 4;
            uint4 u = make_uint4(tag, tag, tag, tag);
            uint32_t pending = live, spins = 0;
            do {
                get4(pending, u, src);
                pending = stale(u, tag);
                if (++spins > SPIN_LIMIT) __trap();
            } while (pending);
            __syncwarp();
            const bool up = lane & 16, b3 = lane & 8;
            const float a0 = __uint_as_float(up ? u.z : u.x) + __shfl_xor_sync(~0u, __uint_as_float(up ? u.x : u.z), 16);
            const float a1 = __uint_as_float(up ? u.w : u.y) + __shfl_xor_sync(~0u, __uint_as_float(up ? u.y : u.w), 16);
            const float r = (b3 ? a1 : a0) + __shfl_xor_sync(~0u, b3 ? a0 : a1, 8);
            sts32(sm + OFF_P + w * 128 + ((lane & 7) * 4 + (lane >> 4) * 2 + ((lane >> 3) & 1)) * 4, __float_as_uint(r));
            consumer_sync();
            if (w == 0) {
                float v[8];
#pragma unroll
                for (int i = 0; i < 8; i++) v[i] = __uint_as_float(lds32(sm + OFF_P + i * 128 + lane * 4));
                const float sv = round_bf16(((v[0] + v[1]) + (v[2] + v[3])) + ((v[4] + v[5]) + (v[6] + v[7])));
                const uint32_t res = pack_bf16(x_res + round_bf16(sv * gate), 0.f);
                asm volatile("{\n.reg .pred p;\n.reg .b16 lo, hi;\nsetp.ne.u32 p, %0, 0;\nmov.b32 {lo, hi}, %2;\n@p st.global.b16 [%1], lo;\n}"
                             ::"r"(live), "l"(out + out_batch * DM + out_col), "r"(res) : "memory");
                if (live && lane == 0) g_epoch[cta] = epoch;
            }
        }
        if (live) break;
    }
}

using EncodeFn = CUresult (*)(CUtensorMap*, CUtensorMapDataType, cuuint32_t, void*, const cuuint64_t*, const cuuint64_t*,
                              const cuuint32_t*, const cuuint32_t*, CUtensorMapInterleave, CUtensorMapSwizzle,
                              CUtensorMapL2promotion, CUtensorMapFloatOOBfill);

void encode(EncodeFn fn, CUtensorMap* m, void* p, cuuint64_t rows, cuuint64_t cols, cuuint32_t box_rows, cuuint32_t box_cols,
            cuuint32_t width = 64) {
    const cuuint64_t dims[3] = {width, rows, cols / width}, strides[2] = {cols * 2, width * 2};
    const cuuint32_t box[3] = {width, box_rows, box_cols / width}, elem[3] = {1, 1, 1};
    fn(m, CU_TENSOR_MAP_DATA_TYPE_BFLOAT16, 3, p, dims, strides, box, elem, CU_TENSOR_MAP_INTERLEAVE_NONE,
       width == 64 ? CU_TENSOR_MAP_SWIZZLE_128B : CU_TENSOR_MAP_SWIZZLE_64B, CU_TENSOR_MAP_L2_PROMOTION_L2_256B,
       CU_TENSOR_MAP_FLOAT_OOB_FILL_NONE);
}

}

extern "C" void kernel_launch(void* const* d_in, const int* in_sizes, int n_in, void* d_out, int out_size) {
    (void)in_sizes; (void)n_in; (void)out_size;
    static EncodeFn fn = nullptr;
    if (!fn) {
        cudaDriverEntryPointQueryResult status;
        cudaGetDriverEntryPoint("cuTensorMapEncodeTiled", (void**)&fn, cudaEnableDefault, &status);
        cudaFuncSetAttribute(decode_kernel, cudaFuncAttributeMaxDynamicSharedMemorySize, SMEM_BYTES);
    }
    Maps maps;
    encode(fn, &maps.m[MAP_K], d_in[1], 8 * 8 * 4096, 128, 64, 128);
    encode(fn, &maps.m[MAP_V], d_in[2], 8 * 8 * 4096, 128, 64, 128);
    encode(fn, &maps.m[MAP_WQ], d_in[3], DM, 4096, 256, 32, 32);
    encode(fn, &maps.m[MAP_WO], d_in[4], 4096, DM, 128, 128);
    encode(fn, &maps.m[MAP_WG], d_in[6], DM, FF, 16, FF_SLICE);
    encode(fn, &maps.m[MAP_WU], d_in[7], DM, FF, 16, FF_SLICE);
    encode(fn, &maps.m[MAP_WD], d_in[8], FF, DM, 16, DM);
    decode_kernel<<<GRID, N_THREADS, SMEM_BYTES>>>(maps, (const __nv_bfloat16*)d_in[0], (__nv_bfloat16*)d_out);
}
```
